```python
import torch

def _softmax(x, axis=-1):
    return torch.softmax(x, dim=axis)
def _gelu(x):
    return torch.nn.functional.gelu(x, approximate="tanh")
def _silu(x):
    return torch.nn.functional.silu(x)
def _sigmoid(x):
    return torch.sigmoid(x)
def _layernorm(x, axis=-1, eps=1e-5):
    m = x.mean(dim=axis, keepdim=True)
    v = x.var(dim=axis, keepdim=True, unbiased=False)
    return (x - m) / torch.sqrt(v + eps)
def _scatter_add(tgt, idx, src, axis=0):
    return tgt.clone().index_add_(axis, idx, src)
def _segment_sum(src, seg, n):
    out = torch.zeros((n,) + src.shape[1:], dtype=src.dtype)
    return out.index_add_(0, seg, src)
def _pad(x, pw):
    flat = tuple(v for pair in reversed(pw) for v in pair)
    return torch.nn.functional.pad(x, flat)

kernel_name = 'recurrent_scan__linear_attn_block__glu_gated_swiglu__prompt'

def setup_inputs():

    _w = (lambda a: (lambda t: t.to(torch.bfloat16) if t.is_floating_point() else t)(torch.as_tensor(a)))
    def _A_setup():
        B, S, D = 1, 2048, 640
        return {
            "x": _w((lambda *s: torch.randn(*s, dtype=torch.bfloat16) * 0.05)(B, S, D)),
            "wqkv": _w((lambda *s: torch.randn(*s, dtype=torch.bfloat16) * 0.8)(D, 3 * D)),
            "wo": _w((lambda *s: torch.randn(*s, dtype=torch.bfloat16) * 0.8)(D, D)),
        }
    _A_in = _A_setup()

    def _B_setup():
        B, S, D, F = 1, 2048, 640, 1728
        return {
            "x": _w((lambda *s: torch.randn(*s, dtype=torch.bfloat16) * 0.05)(B, S, D)),
            "w1": _w((lambda *s: torch.randn(*s, dtype=torch.bfloat16) * 0.2)(D, F) * (2.0 / D) ** 0.5),
            "w3": _w((lambda *s: torch.randn(*s, dtype=torch.bfloat16) * 0.2)(D, F) * (2.0 / D) ** 0.5),
            "w2": _w((lambda *s: torch.randn(*s, dtype=torch.bfloat16) * 0.2)(F, D) * (2.0 / F) ** 0.5),
        }
    _B_in = _B_setup()

    return {
        "A_x": _A_in["x"],
        "A_wqkv": _A_in["wqkv"],
        "A_wo": _A_in["wo"],
        "B_x": _B_in["x"],
        "B_w1": _B_in["w1"],
        "B_w3": _B_in["w3"],
        "B_w2": _B_in["w2"],
    }

def reference(A_x, A_wqkv, A_wo, B_x, B_w1, B_w3, B_w2):
    def _A_ref(x, wqkv, wo):
        B, S, D = x.shape
        H = 32; Dh = D // H
        qkv = (lambda x, *d: x.permute(*d))((x @ wqkv).reshape(B, S, 3, H, Dh), 2, 0, 3, 1, 4)
        q, k, v = qkv[0], qkv[1], qkv[2]
        phi = lambda t: torch.where(t > 0, t + 1, torch.exp(t)) + 1e-6
        pq, pk = phi(q), phi(k)
        kv = torch.einsum("bhsd,bhse->bhde", pk, v)
        z = torch.einsum("bhsd->bhd", pk)
        num = torch.einsum("bhqd,bhde->bhqe", pq, kv)
        den = torch.einsum("bhqd,bhd->bhq", pq, z)[..., None] + 1e-6
        o = num / den
        return (lambda x, *d: x.permute(*d))(o, 0, 2, 1, 3).reshape(B, S, D) @ wo

    def _B_ref(x, w1, w3, w2):
        gate = torch.einsum("bsd,df->bsf", x, w1)
        up = torch.einsum("bsd,df->bsf", x, w3)
        h = _silu(gate) * up
        out = torch.einsum("bsf,fd->bsd", h, w2)
        return out

    x = A_x
    xn = _layernorm(x, axis=-1)
    s = _A_ref(xn, A_wqkv, A_wo)
    g = _silu(_B_ref(xn, B_w1, B_w3, B_w2))
    return x + s * g
```

```cpp
#include <cuda_runtime.h>
#include <cuda_bf16.h>
#include <cuda.h>
#include <stdint.h>

namespace {

constexpr int S_ = 2048, D_ = 640, F_ = 1728;
constexpr int NSLOT = 10, SLOT = 20480;
constexpr int OFF_AUX = NSLOT * SLOT;
constexpr int OFF_BAR = OFF_AUX + 24576;
constexpr int B_EMPTY = 10, B_XFULL = 20, B_XFREE = 30, B_EV = 32, B_KVRDY = 42, B_EP = 43;
constexpr int OFF_EP = OFF_BAR + 48 * 8;
constexpr int OFF_PROF = OFF_EP + 16;
constexpr int SMEM_BYTES = OFF_PROF + 1024;
#define S0 6
constexpr int NY = 66;

__device__ uint4 g_h[16 * 108 * 256];
__device__ uint4 g_o[16 * 40 * 256];
__device__ uint4 g_p[128 * 8 * 5 * 32];
__device__ float g_kv[2 * 8 * 2 * 960];
__device__ unsigned g_cnt[128 * 8];
__device__ unsigned g_epoch[128];
constexpr int C_H = 0, C_O = 48, C_KV = 64;

#define PROFC(i)
#define PROFT(i)
#define PROFT_(i)
#define PROFL(i)
#define PROFEND()

__device__ __forceinline__ uint32_t smem_u32(const void* p) { return (uint32_t)__cvta_generic_to_shared(p); }
__device__ __forceinline__ void mbar_init(uint32_t bar, uint32_t cnt) { asm volatile("mbarrier.init.shared::cta.b64 [%0], %1;" :: "r"(bar), "r"(cnt) : "memory"); }
__device__ __forceinline__ void mbar_expect(uint32_t bar, uint32_t bytes) { asm volatile("mbarrier.arrive.expect_tx.shared::cta.b64 _, [%0], %1;" :: "r"(bar), "r"(bytes) : "memory"); }
__device__ __forceinline__ void mbar_arrive(uint32_t bar) { asm volatile("mbarrier.arrive.shared::cta.b64 _, [%0];" :: "r"(bar) : "memory"); }
__device__ __forceinline__ void mbar_wait(uint32_t bar, uint32_t parity) {
  asm volatile("{\n.reg .pred p;\nLOOP:\nmbarrier.try_wait.parity.shared::cta.b64 p, [%0], %1;\n@!p bra.uni LOOP;\n}" :: "r"(bar), "r"(parity) : "memory");
}
__device__ __forceinline__ void poll_ge(const unsigned* p, unsigned target) {
  #pragma unroll 1
  for (uint32_t n = 0; n < (1u << 20); n++) {
    unsigned v;
    asm volatile("ld.acquire.gpu.global.u32 %0, [%1];" : "=r"(v) : "l"(p) : "memory");
    if ((int)(v - target) >= 0) break;
  }
  asm volatile("fence.proxy.async.global;" ::: "memory");
}
__device__ __forceinline__ void tma2d(uint32_t dst, const CUtensorMap* m, int c0, int c1, uint32_t bar) {
  asm volatile("cp.async.bulk.tensor.2d.shared::cluster.global.mbarrier::complete_tx::bytes [%0], [%1, {%3, %4}], [%2];"
    :: "r"(dst), "l"(m), "r"(bar), "r"(c0), "r"(c1) : "memory");
}
__device__ __forceinline__ void tma3d(uint32_t dst, const CUtensorMap* m, int c0, int c1, int c2, uint32_t bar) {
  asm volatile("cp.async.bulk.tensor.3d.shared::cluster.global.mbarrier::complete_tx::bytes [%0], [%1, {%3, %4, %5}], [%2];"
    :: "r"(dst), "l"(m), "r"(bar), "r"(c0), "r"(c1), "r"(c2) : "memory");
}
__device__ __forceinline__ void bulk(uint32_t dst, const void* src, uint32_t bytes, uint32_t bar) {
  asm volatile("cp.async.bulk.shared::cluster.global.mbarrier::complete_tx::bytes [%0], [%1], %2, [%3];" :: "r"(dst), "l"(src), "r"(bytes), "r"(bar) : "memory");
}
__device__ __forceinline__ void wg_fence() { asm volatile("wgmma.fence.sync.aligned;" ::: "memory"); }
__device__ __forceinline__ void wg_commit() { asm volatile("wgmma.commit_group.sync.aligned;" ::: "memory"); }
template<int N> __device__ __forceinline__ void wg_wait() { asm volatile("wgmma.wait_group.sync.aligned %0;" :: "n"(N) : "memory"); }
template<int O, int N, int L> __device__ __forceinline__ void pin(float (&d)[L]) {
  #pragma unroll
  for (int i = 0; i < N; i++) asm volatile("" : "+f"(d[O + i]) :: "memory");
}
__device__ __forceinline__ int fresh_tid() { int t; asm volatile("mov.u32 %0, %%tid.x;" : "=r"(t)); return t; }
__device__ __forceinline__ uint4 lds128(uint32_t a) { uint4 v; asm volatile("ld.shared.v4.u32 {%0,%1,%2,%3}, [%4];" : "=r"(v.x), "=r"(v.y), "=r"(v.z), "=r"(v.w) : "r"(a) : "memory"); return v; }
__device__ __forceinline__ uint4 ldg_relaxed(const void* p) {
  uint4 v;
  asm volatile("ld.relaxed.gpu.global.v4.u32 {%0, %1, %2, %3}, [%4];" : "=r"(v.x), "=r"(v.y), "=r"(v.z), "=r"(v.w) : "l"(p) : "memory");
  return v;
}
__device__ __forceinline__ void stg_relaxed(void* p, uint32_t x, uint32_t y, uint32_t z, uint32_t w) {
  asm volatile("st.relaxed.gpu.global.v4.u32 [%0], {%1, %2, %3, %4};" :: "l"(p), "r"(x), "r"(y), "r"(z), "r"(w) : "memory");
}
__device__ __forceinline__ void sts128(uint32_t a, uint32_t x, uint32_t y, uint32_t z, uint32_t w) {
  asm volatile("st.shared.v4.u32 [%0], {%1,%2,%3,%4};" :: "r"(a), "r"(x), "r"(y), "r"(z), "r"(w) : "memory");
}
__device__ __forceinline__ void stsm4(uint32_t a, uint32_t r0, uint32_t r1, uint32_t r2, uint32_t r3) {
  asm volatile("stmatrix.sync.aligned.m8n8.x4.shared.b16 [%0], {%1,%2,%3,%4};" :: "r"(a), "r"(r0), "r"(r1), "r"(r2), "r"(r3) : "memory");
}
__device__ __forceinline__ uint32_t pack(float lo, float hi) { uint32_t r; asm("cvt.rn.bf16x2.f32 %0, %1, %2;" : "=r"(r) : "f"(hi), "f"(lo)); return r; }
__device__ __forceinline__ float blo(uint32_t v) { return __uint_as_float(v << 16); }
__device__ __forceinline__ float bhi(uint32_t v) { return __uint_as_float(v & 0xffff0000u); }
__device__ __forceinline__ float ex2(float x) { float y; asm("ex2.approx.ftz.f32 %0, %1;" : "=f"(y) : "f"(x)); return y; }
__device__ __forceinline__ float rcp(float x) { float y; asm("rcp.approx.ftz.f32 %0, %1;" : "=f"(y) : "f"(x)); return y; }
__device__ __forceinline__ float tanh_(float x) { float y; asm("tanh.approx.f32 %0, %1;" : "=f"(y) : "f"(x)); return y; }
__device__ __forceinline__ uint32_t hmul(uint32_t a, uint32_t b) { uint32_t r; asm("mul.rn.bf16x2 %0, %1, %2;" : "=r"(r) : "r"(a), "r"(b)); return r; }
__device__ __forceinline__ uint32_t hfma(uint32_t a, uint32_t b, uint32_t c) { uint32_t r; asm("fma.rn.bf16x2 %0, %1, %2, %3;" : "=r"(r) : "r"(a), "r"(b), "r"(c)); return r; }
__device__ __forceinline__ void rowsum(float (&d)[4], uint32_t a0, uint32_t a1, uint32_t a2, uint32_t a3) {
  asm volatile("mma.sync.aligned.m16n8k16.row.col.f32.bf16.bf16.f32 {%0,%1,%2,%3}, {%4,%5,%6,%7}, {%8,%8}, {%0,%1,%2,%3};"
               : "+f"(d[0]), "+f"(d[1]), "+f"(d[2]), "+f"(d[3]) : "r"(a0), "r"(a1), "r"(a2), "r"(a3), "r"(0x3f803f80u));
}
constexpr float LOG2E = 1.4426950408889634f;
__device__ __forceinline__ uint32_t phi2(float u, float v, float r, float k) {
  return pack((u > 0.f ? fmaf(u, r, 1.f) : ex2(u * k)) + 1e-6f, (v > 0.f ? fmaf(v, r, 1.f) : ex2(v * k)) + 1e-6f);
}
__device__ __forceinline__ float silu2(float h) { return fmaf(h, tanh_(h), h); }

template<int O, int SD, int L> __device__ __forceinline__ void rs96(float (&d)[L], uint32_t a0, uint32_t a1, uint32_t a2, uint32_t a3, uint64_t& db, uint32_t st) {
  if (SD) asm volatile("{\n.reg .pred p;\nsetp.ne.b32 p, 1, 0;\n"
    "wgmma.mma_async.sync.aligned.m64n96k16.f32.bf16.bf16 {%0, %1, %2, %3, %4, %5, %6, %7, %8, %9, %10, %11, %12, %13, %14, %15, %16, %17, %18, %19, %20, %21, %22, %23, %24, %25, %26, %27, %28, %29, %30, %31, %32, %33, %34, %35, %36, %37, %38, %39, %40, %41, %42, %43, %44, %45, %46, %47}, {%48, %49, %50, %51}, %52, p, 1, 1, 1;\n}\n"
    : "+f"(d[O + 0]), "+f"(d[O + 1]), "+f"(d[O + 2]), "+f"(d[O + 3]), "+f"(d[O + 4]), "+f"(d[O + 5]), "+f"(d[O + 6]), "+f"(d[O + 7]), "+f"(d[O + 8]), "+f"(d[O + 9]), "+f"(d[O + 10]), "+f"(d[O + 11]), "+f"(d[O + 12]), "+f"(d[O + 13]), "+f"(d[O + 14]), "+f"(d[O + 15]), "+f"(d[O + 16]), "+f"(d[O + 17]), "+f"(d[O + 18]), "+f"(d[O + 19]), "+f"(d[O + 20]), "+f"(d[O + 21]), "+f"(d[O + 22]), "+f"(d[O + 23]), "+f"(d[O + 24]), "+f"(d[O + 25]), "+f"(d[O + 26]), "+f"(d[O + 27]), "+f"(d[O + 28]), "+f"(d[O + 29]), "+f"(d[O + 30]), "+f"(d[O + 31]), "+f"(d[O + 32]), "+f"(d[O + 33]), "+f"(d[O + 34]), "+f"(d[O + 35]), "+f"(d[O + 36]), "+f"(d[O + 37]), "+f"(d[O + 38]), "+f"(d[O + 39]), "+f"(d[O + 40]), "+f"(d[O + 41]), "+f"(d[O + 42]), "+f"(d[O + 43]), "+f"(d[O + 44]), "+f"(d[O + 45]), "+f"(d[O + 46]), "+f"(d[O + 47])
    : "r"(a0), "r"(a1), "r"(a2), "r"(a3), "l"(db));
  else asm volatile("{\n.reg .pred p;\nsetp.ne.b32 p, 0, 0;\n"
    "wgmma.mma_async.sync.aligned.m64n96k16.f32.bf16.bf16 {%0, %1, %2, %3, %4, %5, %6, %7, %8, %9, %10, %11, %12, %13, %14, %15, %16, %17, %18, %19, %20, %21, %22, %23, %24, %25, %26, %27, %28, %29, %30, %31, %32, %33, %34, %35, %36, %37, %38, %39, %40, %41, %42, %43, %44, %45, %46, %47}, {%48, %49, %50, %51}, %52, p, 1, 1, 1;\n}\n"
    : "=f"(d[O + 0]), "=f"(d[O + 1]), "=f"(d[O + 2]), "=f"(d[O + 3]), "=f"(d[O + 4]), "=f"(d[O + 5]), "=f"(d[O + 6]), "=f"(d[O + 7]), "=f"(d[O + 8]), "=f"(d[O + 9]), "=f"(d[O + 10]), "=f"(d[O + 11]), "=f"(d[O + 12]), "=f"(d[O + 13]), "=f"(d[O + 14]), "=f"(d[O + 15]), "=f"(d[O + 16]), "=f"(d[O + 17]), "=f"(d[O + 18]), "=f"(d[O + 19]), "=f"(d[O + 20]), "=f"(d[O + 21]), "=f"(d[O + 22]), "=f"(d[O + 23]), "=f"(d[O + 24]), "=f"(d[O + 25]), "=f"(d[O + 26]), "=f"(d[O + 27]), "=f"(d[O + 28]), "=f"(d[O + 29]), "=f"(d[O + 30]), "=f"(d[O + 31]), "=f"(d[O + 32]), "=f"(d[O + 33]), "=f"(d[O + 34]), "=f"(d[O + 35]), "=f"(d[O + 36]), "=f"(d[O + 37]), "=f"(d[O + 38]), "=f"(d[O + 39]), "=f"(d[O + 40]), "=f"(d[O + 41]), "=f"(d[O + 42]), "=f"(d[O + 43]), "=f"(d[O + 44]), "=f"(d[O + 45]), "=f"(d[O + 46]), "=f"(d[O + 47])
    : "r"(a0), "r"(a1), "r"(a2), "r"(a3), "l"(db));
  db += st;
}
template<int O, int SD, int L> __device__ __forceinline__ void rs48(float (&d)[L], uint32_t a0, uint32_t a1, uint32_t a2, uint32_t a3, uint64_t& db, uint32_t st) {
  if (SD) asm volatile("{\n.reg .pred p;\nsetp.ne.b32 p, 1, 0;\n"
    "wgmma.mma_async.sync.aligned.m64n48k16.f32.bf16.bf16 {%0, %1, %2, %3, %4, %5, %6, %7, %8, %9, %10, %11, %12, %13, %14, %15, %16, %17, %18, %19, %20, %21, %22, %23}, {%24, %25, %26, %27}, %28, p, 1, 1, 1;\n}\n"
    : "+f"(d[O + 0]), "+f"(d[O + 1]), "+f"(d[O + 2]), "+f"(d[O + 3]), "+f"(d[O + 4]), "+f"(d[O + 5]), "+f"(d[O + 6]), "+f"(d[O + 7]), "+f"(d[O + 8]), "+f"(d[O + 9]), "+f"(d[O + 10]), "+f"(d[O + 11]), "+f"(d[O + 12]), "+f"(d[O + 13]), "+f"(d[O + 14]), "+f"(d[O + 15]), "+f"(d[O + 16]), "+f"(d[O + 17]), "+f"(d[O + 18]), "+f"(d[O + 19]), "+f"(d[O + 20]), "+f"(d[O + 21]), "+f"(d[O + 22]), "+f"(d[O + 23])
    : "r"(a0), "r"(a1), "r"(a2), "r"(a3), "l"(db));
  else asm volatile("{\n.reg .pred p;\nsetp.ne.b32 p, 0, 0;\n"
    "wgmma.mma_async.sync.aligned.m64n48k16.f32.bf16.bf16 {%0, %1, %2, %3, %4, %5, %6, %7, %8, %9, %10, %11, %12, %13, %14, %15, %16, %17, %18, %19, %20, %21, %22, %23}, {%24, %25, %26, %27}, %28, p, 1, 1, 1;\n}\n"
    : "=f"(d[O + 0]), "=f"(d[O + 1]), "=f"(d[O + 2]), "=f"(d[O + 3]), "=f"(d[O + 4]), "=f"(d[O + 5]), "=f"(d[O + 6]), "=f"(d[O + 7]), "=f"(d[O + 8]), "=f"(d[O + 9]), "=f"(d[O + 10]), "=f"(d[O + 11]), "=f"(d[O + 12]), "=f"(d[O + 13]), "=f"(d[O + 14]), "=f"(d[O + 15]), "=f"(d[O + 16]), "=f"(d[O + 17]), "=f"(d[O + 18]), "=f"(d[O + 19]), "=f"(d[O + 20]), "=f"(d[O + 21]), "=f"(d[O + 22]), "=f"(d[O + 23])
    : "r"(a0), "r"(a1), "r"(a2), "r"(a3), "l"(db));
  db += st;
}
template<int O, int SD, int L> __device__ __forceinline__ void rs128(float (&d)[L], uint32_t a0, uint32_t a1, uint32_t a2, uint32_t a3, uint64_t& db, uint32_t st) {
  if (SD) asm volatile("{\n.reg .pred p;\nsetp.ne.b32 p, 1, 0;\n"
    "wgmma.mma_async.sync.aligned.m64n128k16.f32.bf16.bf16 {%0, %1, %2, %3, %4, %5, %6, %7, %8, %9, %10, %11, %12, %13, %14, %15, %16, %17, %18, %19, %20, %21, %22, %23, %24, %25, %26, %27, %28, %29, %30, %31, %32, %33, %34, %35, %36, %37, %38, %39, %40, %41, %42, %43, %44, %45, %46, %47, %48, %49, %50, %51, %52, %53, %54, %55, %56, %57, %58, %59, %60, %61, %62, %63}, {%64, %65, %66, %67}, %68, p, 1, 1, 1;\n}\n"
    : "+f"(d[O + 0]), "+f"(d[O + 1]), "+f"(d[O + 2]), "+f"(d[O + 3]), "+f"(d[O + 4]), "+f"(d[O + 5]), "+f"(d[O + 6]), "+f"(d[O + 7]), "+f"(d[O + 8]), "+f"(d[O + 9]), "+f"(d[O + 10]), "+f"(d[O + 11]), "+f"(d[O + 12]), "+f"(d[O + 13]), "+f"(d[O + 14]), "+f"(d[O + 15]), "+f"(d[O + 16]), "+f"(d[O + 17]), "+f"(d[O + 18]), "+f"(d[O + 19]), "+f"(d[O + 20]), "+f"(d[O + 21]), "+f"(d[O + 22]), "+f"(d[O + 23]), "+f"(d[O + 24]), "+f"(d[O + 25]), "+f"(d[O + 26]), "+f"(d[O + 27]), "+f"(d[O + 28]), "+f"(d[O + 29]), "+f"(d[O + 30]), "+f"(d[O + 31]), "+f"(d[O + 32]), "+f"(d[O + 33]), "+f"(d[O + 34]), "+f"(d[O + 35]), "+f"(d[O + 36]), "+f"(d[O + 37]), "+f"(d[O + 38]), "+f"(d[O + 39]), "+f"(d[O + 40]), "+f"(d[O + 41]), "+f"(d[O + 42]), "+f"(d[O + 43]), "+f"(d[O + 44]), "+f"(d[O + 45]), "+f"(d[O + 46]), "+f"(d[O + 47]), "+f"(d[O + 48]), "+f"(d[O + 49]), "+f"(d[O + 50]), "+f"(d[O + 51]), "+f"(d[O + 52]), "+f"(d[O + 53]), "+f"(d[O + 54]), "+f"(d[O + 55]), "+f"(d[O + 56]), "+f"(d[O + 57]), "+f"(d[O + 58]), "+f"(d[O + 59]), "+f"(d[O + 60]), "+f"(d[O + 61]), "+f"(d[O + 62]), "+f"(d[O + 63])
    : "r"(a0), "r"(a1), "r"(a2), "r"(a3), "l"(db));
  else asm volatile("{\n.reg .pred p;\nsetp.ne.b32 p, 0, 0;\n"
    "wgmma.mma_async.sync.aligned.m64n128k16.f32.bf16.bf16 {%0, %1, %2, %3, %4, %5, %6, %7, %8, %9, %10, %11, %12, %13, %14, %15, %16, %17, %18, %19, %20, %21, %22, %23, %24, %25, %26, %27, %28, %29, %30, %31, %32, %33, %34, %35, %36, %37, %38, %39, %40, %41, %42, %43, %44, %45, %46, %47, %48, %49, %50, %51, %52, %53, %54, %55, %56, %57, %58, %59, %60, %61, %62, %63}, {%64, %65, %66, %67}, %68, p, 1, 1, 1;\n}\n"
    : "=f"(d[O + 0]), "=f"(d[O + 1]), "=f"(d[O + 2]), "=f"(d[O + 3]), "=f"(d[O + 4]), "=f"(d[O + 5]), "=f"(d[O + 6]), "=f"(d[O + 7]), "=f"(d[O + 8]), "=f"(d[O + 9]), "=f"(d[O + 10]), "=f"(d[O + 11]), "=f"(d[O + 12]), "=f"(d[O + 13]), "=f"(d[O + 14]), "=f"(d[O + 15]), "=f"(d[O + 16]), "=f"(d[O + 17]), "=f"(d[O + 18]), "=f"(d[O + 19]), "=f"(d[O + 20]), "=f"(d[O + 21]), "=f"(d[O + 22]), "=f"(d[O + 23]), "=f"(d[O + 24]), "=f"(d[O + 25]), "=f"(d[O + 26]), "=f"(d[O + 27]), "=f"(d[O + 28]), "=f"(d[O + 29]), "=f"(d[O + 30]), "=f"(d[O + 31]), "=f"(d[O + 32]), "=f"(d[O + 33]), "=f"(d[O + 34]), "=f"(d[O + 35]), "=f"(d[O + 36]), "=f"(d[O + 37]), "=f"(d[O + 38]), "=f"(d[O + 39]), "=f"(d[O + 40]), "=f"(d[O + 41]), "=f"(d[O + 42]), "=f"(d[O + 43]), "=f"(d[O + 44]), "=f"(d[O + 45]), "=f"(d[O + 46]), "=f"(d[O + 47]), "=f"(d[O + 48]), "=f"(d[O + 49]), "=f"(d[O + 50]), "=f"(d[O + 51]), "=f"(d[O + 52]), "=f"(d[O + 53]), "=f"(d[O + 54]), "=f"(d[O + 55]), "=f"(d[O + 56]), "=f"(d[O + 57]), "=f"(d[O + 58]), "=f"(d[O + 59]), "=f"(d[O + 60]), "=f"(d[O + 61]), "=f"(d[O + 62]), "=f"(d[O + 63])
    : "r"(a0), "r"(a1), "r"(a2), "r"(a3), "l"(db));
  db += st;
}
template<int O, int SD, int L> __device__ __forceinline__ void rs32(float (&d)[L], uint32_t a0, uint32_t a1, uint32_t a2, uint32_t a3, uint64_t& db, uint32_t st) {
  if (SD) asm volatile("{\n.reg .pred p;\nsetp.ne.b32 p, 1, 0;\n"
    "wgmma.mma_async.sync.aligned.m64n32k16.f32.bf16.bf16 {%0, %1, %2, %3, %4, %5, %6, %7, %8, %9, %10, %11, %12, %13, %14, %15}, {%16, %17, %18, %19}, %20, p, 1, 1, 1;\n}\n"
    : "+f"(d[O + 0]), "+f"(d[O + 1]), "+f"(d[O + 2]), "+f"(d[O + 3]), "+f"(d[O + 4]), "+f"(d[O + 5]), "+f"(d[O + 6]), "+f"(d[O + 7]), "+f"(d[O + 8]), "+f"(d[O + 9]), "+f"(d[O + 10]), "+f"(d[O + 11]), "+f"(d[O + 12]), "+f"(d[O + 13]), "+f"(d[O + 14]), "+f"(d[O + 15])
    : "r"(a0), "r"(a1), "r"(a2), "r"(a3), "l"(db));
  else asm volatile("{\n.reg .pred p;\nsetp.ne.b32 p, 0, 0;\n"
    "wgmma.mma_async.sync.aligned.m64n32k16.f32.bf16.bf16 {%0, %1, %2, %3, %4, %5, %6, %7, %8, %9, %10, %11, %12, %13, %14, %15}, {%16, %17, %18, %19}, %20, p, 1, 1, 1;\n}\n"
    : "=f"(d[O + 0]), "=f"(d[O + 1]), "=f"(d[O + 2]), "=f"(d[O + 3]), "=f"(d[O + 4]), "=f"(d[O + 5]), "=f"(d[O + 6]), "=f"(d[O + 7]), "=f"(d[O + 8]), "=f"(d[O + 9]), "=f"(d[O + 10]), "=f"(d[O + 11]), "=f"(d[O + 12]), "=f"(d[O + 13]), "=f"(d[O + 14]), "=f"(d[O + 15])
    : "r"(a0), "r"(a1), "r"(a2), "r"(a3), "l"(db));
  db += st;
}
template<int O, int SD, int L> __device__ __forceinline__ void rs80(float (&d)[L], uint32_t a0, uint32_t a1, uint32_t a2, uint32_t a3, uint64_t& db, uint32_t st) {
  if (SD) asm volatile("{\n.reg .pred p;\nsetp.ne.b32 p, 1, 0;\n"
    "wgmma.mma_async.sync.aligned.m64n80k16.f32.bf16.bf16 {%0, %1, %2, %3, %4, %5, %6, %7, %8, %9, %10, %11, %12, %13, %14, %15, %16, %17, %18, %19, %20, %21, %22, %23, %24, %25, %26, %27, %28, %29, %30, %31, %32, %33, %34, %35, %36, %37, %38, %39}, {%40, %41, %42, %43}, %44, p, 1, 1, 1;\n}\n"
    : "+f"(d[O + 0]), "+f"(d[O + 1]), "+f"(d[O + 2]), "+f"(d[O + 3]), "+f"(d[O + 4]), "+f"(d[O + 5]), "+f"(d[O + 6]), "+f"(d[O + 7]), "+f"(d[O + 8]), "+f"(d[O + 9]), "+f"(d[O + 10]), "+f"(d[O + 11]), "+f"(d[O + 12]), "+f"(d[O + 13]), "+f"(d[O + 14]), "+f"(d[O + 15]), "+f"(d[O + 16]), "+f"(d[O + 17]), "+f"(d[O + 18]), "+f"(d[O + 19]), "+f"(d[O + 20]), "+f"(d[O + 21]), "+f"(d[O + 22]), "+f"(d[O + 23]), "+f"(d[O + 24]), "+f"(d[O + 25]), "+f"(d[O + 26]), "+f"(d[O + 27]), "+f"(d[O + 28]), "+f"(d[O + 29]), "+f"(d[O + 30]), "+f"(d[O + 31]), "+f"(d[O + 32]), "+f"(d[O + 33]), "+f"(d[O + 34]), "+f"(d[O + 35]), "+f"(d[O + 36]), "+f"(d[O + 37]), "+f"(d[O + 38]), "+f"(d[O + 39])
    : "r"(a0), "r"(a1), "r"(a2), "r"(a3), "l"(db));
  else asm volatile("{\n.reg .pred p;\nsetp.ne.b32 p, 0, 0;\n"
    "wgmma.mma_async.sync.aligned.m64n80k16.f32.bf16.bf16 {%0, %1, %2, %3, %4, %5, %6, %7, %8, %9, %10, %11, %12, %13, %14, %15, %16, %17, %18, %19, %20, %21, %22, %23, %24, %25, %26, %27, %28, %29, %30, %31, %32, %33, %34, %35, %36, %37, %38, %39}, {%40, %41, %42, %43}, %44, p, 1, 1, 1;\n}\n"
    : "=f"(d[O + 0]), "=f"(d[O + 1]), "=f"(d[O + 2]), "=f"(d[O + 3]), "=f"(d[O + 4]), "=f"(d[O + 5]), "=f"(d[O + 6]), "=f"(d[O + 7]), "=f"(d[O + 8]), "=f"(d[O + 9]), "=f"(d[O + 10]), "=f"(d[O + 11]), "=f"(d[O + 12]), "=f"(d[O + 13]), "=f"(d[O + 14]), "=f"(d[O + 15]), "=f"(d[O + 16]), "=f"(d[O + 17]), "=f"(d[O + 18]), "=f"(d[O + 19]), "=f"(d[O + 20]), "=f"(d[O + 21]), "=f"(d[O + 22]), "=f"(d[O + 23]), "=f"(d[O + 24]), "=f"(d[O + 25]), "=f"(d[O + 26]), "=f"(d[O + 27]), "=f"(d[O + 28]), "=f"(d[O + 29]), "=f"(d[O + 30]), "=f"(d[O + 31]), "=f"(d[O + 32]), "=f"(d[O + 33]), "=f"(d[O + 34]), "=f"(d[O + 35]), "=f"(d[O + 36]), "=f"(d[O + 37]), "=f"(d[O + 38]), "=f"(d[O + 39])
    : "r"(a0), "r"(a1), "r"(a2), "r"(a3), "l"(db));
  db += st;
}
template<int O, int SD, int L> __device__ __forceinline__ void rs88k(float (&d)[L], uint32_t a0, uint32_t a1, uint32_t a2, uint32_t a3, uint64_t& db, uint32_t st) {
  if (SD) asm volatile("{\n.reg .pred p;\nsetp.ne.b32 p, 1, 0;\n"
    "wgmma.mma_async.sync.aligned.m64n88k16.f32.bf16.bf16 {%0, %1, %2, %3, %4, %5, %6, %7, %8, %9, %10, %11, %12, %13, %14, %15, %16, %17, %18, %19, %20, %21, %22, %23, %24, %25, %26, %27, %28, %29, %30, %31, %32, %33, %34, %35, %36, %37, %38, %39, %40, %41, %42, %43}, {%44, %45, %46, %47}, %48, p, 1, 1, 0;\n}\n"
    : "+f"(d[O + 0]), "+f"(d[O + 1]), "+f"(d[O + 2]), "+f"(d[O + 3]), "+f"(d[O + 4]), "+f"(d[O + 5]), "+f"(d[O + 6]), "+f"(d[O + 7]), "+f"(d[O + 8]), "+f"(d[O + 9]), "+f"(d[O + 10]), "+f"(d[O + 11]), "+f"(d[O + 12]), "+f"(d[O + 13]), "+f"(d[O + 14]), "+f"(d[O + 15]), "+f"(d[O + 16]), "+f"(d[O + 17]), "+f"(d[O + 18]), "+f"(d[O + 19]), "+f"(d[O + 20]), "+f"(d[O + 21]), "+f"(d[O + 22]), "+f"(d[O + 23]), "+f"(d[O + 24]), "+f"(d[O + 25]), "+f"(d[O + 26]), "+f"(d[O + 27]), "+f"(d[O + 28]), "+f"(d[O + 29]), "+f"(d[O + 30]), "+f"(d[O + 31]), "+f"(d[O + 32]), "+f"(d[O + 33]), "+f"(d[O + 34]), "+f"(d[O + 35]), "+f"(d[O + 36]), "+f"(d[O + 37]), "+f"(d[O + 38]), "+f"(d[O + 39]), "+f"(d[O + 40]), "+f"(d[O + 41]), "+f"(d[O + 42]), "+f"(d[O + 43])
    : "r"(a0), "r"(a1), "r"(a2), "r"(a3), "l"(db));
  else asm volatile("{\n.reg .pred p;\nsetp.ne.b32 p, 0, 0;\n"
    "wgmma.mma_async.sync.aligned.m64n88k16.f32.bf16.bf16 {%0, %1, %2, %3, %4, %5, %6, %7, %8, %9, %10, %11, %12, %13, %14, %15, %16, %17, %18, %19, %20, %21, %22, %23, %24, %25, %26, %27, %28, %29, %30, %31, %32, %33, %34, %35, %36, %37, %38, %39, %40, %41, %42, %43}, {%44, %45, %46, %47}, %48, p, 1, 1, 0;\n}\n"
    : "=f"(d[O + 0]), "=f"(d[O + 1]), "=f"(d[O + 2]), "=f"(d[O + 3]), "=f"(d[O + 4]), "=f"(d[O + 5]), "=f"(d[O + 6]), "=f"(d[O + 7]), "=f"(d[O + 8]), "=f"(d[O + 9]), "=f"(d[O + 10]), "=f"(d[O + 11]), "=f"(d[O + 12]), "=f"(d[O + 13]), "=f"(d[O + 14]), "=f"(d[O + 15]), "=f"(d[O + 16]), "=f"(d[O + 17]), "=f"(d[O + 18]), "=f"(d[O + 19]), "=f"(d[O + 20]), "=f"(d[O + 21]), "=f"(d[O + 22]), "=f"(d[O + 23]), "=f"(d[O + 24]), "=f"(d[O + 25]), "=f"(d[O + 26]), "=f"(d[O + 27]), "=f"(d[O + 28]), "=f"(d[O + 29]), "=f"(d[O + 30]), "=f"(d[O + 31]), "=f"(d[O + 32]), "=f"(d[O + 33]), "=f"(d[O + 34]), "=f"(d[O + 35]), "=f"(d[O + 36]), "=f"(d[O + 37]), "=f"(d[O + 38]), "=f"(d[O + 39]), "=f"(d[O + 40]), "=f"(d[O + 41]), "=f"(d[O + 42]), "=f"(d[O + 43])
    : "r"(a0), "r"(a1), "r"(a2), "r"(a3), "l"(db));
  db += st;
}
template<int O, uint32_t HI, int SD, int L> __device__ __forceinline__ void ss48tt(float (&d)[L], uint32_t alo, uint32_t blo) {
  if (SD) asm volatile("{\n.reg .pred p;\n.reg .b64 da, db;\nsetp.ne.b32 p, 1, 0;\nmov.b64 da, {%24, %26};\nmov.b64 db, {%25, %26};\n"
    "wgmma.mma_async.sync.aligned.m64n48k16.f32.bf16.bf16 {%0, %1, %2, %3, %4, %5, %6, %7, %8, %9, %10, %11, %12, %13, %14, %15, %16, %17, %18, %19, %20, %21, %22, %23}, da, db, p, 1, 1, 1, 1;\n}\n"
    : "+f"(d[O + 0]), "+f"(d[O + 1]), "+f"(d[O + 2]), "+f"(d[O + 3]), "+f"(d[O + 4]), "+f"(d[O + 5]), "+f"(d[O + 6]), "+f"(d[O + 7]), "+f"(d[O + 8]), "+f"(d[O + 9]), "+f"(d[O + 10]), "+f"(d[O + 11]), "+f"(d[O + 12]), "+f"(d[O + 13]), "+f"(d[O + 14]), "+f"(d[O + 15]), "+f"(d[O + 16]), "+f"(d[O + 17]), "+f"(d[O + 18]), "+f"(d[O + 19]), "+f"(d[O + 20]), "+f"(d[O + 21]), "+f"(d[O + 22]), "+f"(d[O + 23])
    : "r"(alo), "r"(blo), "n"(HI));
  else asm volatile("{\n.reg .pred p;\n.reg .b64 da, db;\nsetp.ne.b32 p, 0, 0;\nmov.b64 da, {%24, %26};\nmov.b64 db, {%25, %26};\n"
    "wgmma.mma_async.sync.aligned.m64n48k16.f32.bf16.bf16 {%0, %1, %2, %3, %4, %5, %6, %7, %8, %9, %10, %11, %12, %13, %14, %15, %16, %17, %18, %19, %20, %21, %22, %23}, da, db, p, 1, 1, 1, 1;\n}\n"
    : "=f"(d[O + 0]), "=f"(d[O + 1]), "=f"(d[O + 2]), "=f"(d[O + 3]), "=f"(d[O + 4]), "=f"(d[O + 5]), "=f"(d[O + 6]), "=f"(d[O + 7]), "=f"(d[O + 8]), "=f"(d[O + 9]), "=f"(d[O + 10]), "=f"(d[O + 11]), "=f"(d[O + 12]), "=f"(d[O + 13]), "=f"(d[O + 14]), "=f"(d[O + 15]), "=f"(d[O + 16]), "=f"(d[O + 17]), "=f"(d[O + 18]), "=f"(d[O + 19]), "=f"(d[O + 20]), "=f"(d[O + 21]), "=f"(d[O + 22]), "=f"(d[O + 23])
    : "r"(alo), "r"(blo), "n"(HI));
}

constexpr uint32_t HI128 = 0x40000040u;
constexpr uint32_t HI64 = 0x80000020u;
constexpr uint32_t HI32 = 0xC0000010u;

__device__ __forceinline__ uint64_t desc(uint32_t lo, uint32_t hi) { return (uint64_t)hi << 32 | lo; }
__device__ __forceinline__ bool elect() {
  uint32_t p;
  asm volatile("{\n.reg .pred p;\nelect.sync _|p, 0xffffffff;\nselp.u32 %0, 1, 0, p;\n}" : "=r"(p));
  return p;
}
struct Ring {
  uint32_t fb, lo, ph;
  __device__ __forceinline__ void at(uint32_t it, uint32_t base) {
    const uint32_t rev = (it * 205u) >> 11, slot = it - rev * NSLOT;
    fb = base + OFF_BAR + 8 * slot; lo = (base >> 4) + slot * (SLOT / 16); ph = rev & 1;
  }
  template<int N> __device__ __forceinline__ void next(uint32_t bars) {
    fb += 8 * N; lo += N * (SLOT / 16);
    if (fb >= bars + 8 * NSLOT) { fb -= 8 * NSLOT; lo -= NSLOT * (SLOT / 16); ph ^= 1; }
  }
};

template<int N>
__device__ __forceinline__ void tile_mma(float (&acc)[48], const uint32_t (&a)[160], int t, uint32_t base, bool lane0, uint32_t sig) {
  const uint32_t bars = base + OFF_BAR;
  uint32_t prev = 0;
  Ring r;
  r.at(8 * t + (t >= 2 ? 2 : 0), base);
  mbar_wait(r.fb, r.ph);
  #pragma unroll
  for (int st = 0; st < 8; st++) {
    uint64_t db = desc(r.lo | (640u << 16), HI128), d2 = desc(r.lo + 640, HI128);
    const uint32_t cur = r.fb;
    wg_fence();
    #pragma unroll
    for (int kk = 0; kk < 5; kk++) {
      const int k = 4 * (st * 5 + kk);
      if (k == 0) {
        if (N == 80) rs80<0, 0>(acc, a[k], a[k + 1], a[k + 2], a[k + 3], db, 128);
        else if (N == 96) rs96<0, 0>(acc, a[k], a[k + 1], a[k + 2], a[k + 3], db, 128);
        else { rs48<0, 0>(acc, a[k], a[k + 1], a[k + 2], a[k + 3], db, 128); rs48<24, 0>(acc, a[k], a[k + 1], a[k + 2], a[k + 3], d2, 128); }
      } else {
        if (N == 80) rs80<0, 1>(acc, a[k], a[k + 1], a[k + 2], a[k + 3], db, 128);
        else if (N == 96) rs96<0, 1>(acc, a[k], a[k + 1], a[k + 2], a[k + 3], db, 128);
        else { rs48<0, 1>(acc, a[k], a[k + 1], a[k + 2], a[k + 3], db, 128); rs48<24, 1>(acc, a[k], a[k + 1], a[k + 2], a[k + 3], d2, 128); }
      }
    }
    wg_commit();
    if (st == S0 - 1) asm volatile("bar.arrive %0, 256;" :: "r"(sig) : "memory");
    r.next<1>(bars);
    if (st > 0) { wg_wait<1>(); if (lane0) mbar_arrive(prev + 80); }
    if (st < 7) mbar_wait(r.fb, r.ph);
    prev = cur;
  }
  wg_wait<0>();
  if (lane0) mbar_arrive(prev + 80);
  pin<0, N == 80 ? 40 : 48>(acc);
}

struct Maps { CUtensorMap x, qkv64, qkv16, w1a, w1b, w3a, w3b, w1c, w3c, w2a, w2b, woa, wob; };

__global__ void __launch_bounds__(384, 1)
fused_kernel(const __grid_constant__ Maps M, const __nv_bfloat16* __restrict__ x, __nv_bfloat16* __restrict__ out) {
  extern __shared__ __align__(1024) uint8_t smem_raw[];
  const uint32_t base = (smem_u32(smem_raw) + 1023) & ~1023u;
  const uint32_t bars = base + OFF_BAR;
  const int tid = threadIdx.x;
  const int warp = __shfl_sync(0xffffffffu, tid >> 5, 0);
  const int b = blockIdx.x;
  const int rb = ((b >> 4) & 3) * 4 + ((b & 15) >> 2), role = b >> 6, p = b & 3, g = 2 * p + role;
  const int nt = role ? 7 : 8;
  const int cl = 160 * p + (p & 1) * 32, ch = 160 * p + (~p & 1) * 128;

  const bool el = elect();
  if (warp == 8 && el) {
    PROFT_(0);
    #pragma unroll
    for (int i = 0; i < 5; i++) mbar_init(bars + 8 * (B_XFULL + i), 1);
    asm volatile("fence.proxy.async.shared::cta;" ::: "memory");
    #pragma unroll
    for (int i = 0; i < 5; i++) {
      mbar_expect(bars + 8 * (B_XFULL + i), 16384);
      tma3d(base + 3 * SLOT + i * 16384, &M.x, 0, rb * 128, 2 * i, bars + 8 * (B_XFULL + i));
    }
  } else if (warp == 9 && el) {
    #pragma unroll
    for (int i = 0; i < 20; i++) mbar_init(bars + 8 * i, i < 10 ? 1 : 8);
    asm volatile("fence.proxy.async.shared::cta;" ::: "memory");
  } else if (warp == 10 && el) {
    #pragma unroll
    for (int i = 25; i < 44; i++) mbar_init(bars + 8 * i, i < 30 ? 1 : i < 42 ? 4 : i == B_KVRDY ? 2 : 1);
    asm volatile("fence.proxy.async.shared::cta;" ::: "memory");
  } else if (warp == 11 && el) {
    #pragma unroll 1
    for (int i = 1; i < 13; i++) asm volatile("prefetch.tensormap [%0];" :: "l"(&M.x + i) : "memory");
  }
  __syncthreads();

  if (warp < 8) goto CONSUMER;
  asm volatile("setmaxnreg.dec.sync.aligned.u32 24;");
  if (warp >= 10) goto PUBLISHER;
  {
      if (elect()) {
        const int w = warp - 8;
        Ring r{bars + 8 * w, (base + w * SLOT) >> 4, 1};
        uint32_t fb, dst;
        auto acquire = [&](uint32_t bytes) {
          mbar_wait(r.fb + 80, r.ph);
          fb = r.fb; dst = r.lo << 4;
          mbar_expect(fb, bytes);
          r.next<2>(bars);
        };
        #pragma unroll 1
        for (int t = 0; t < nt; t++) {
          const CUtensorMap* m0 = &M.qkv64; const CUtensorMap* m1 = &M.qkv16;
          int c0, c1; uint32_t bytes = 15360;
          if (t < 2 || t == nt - 1) { c0 = (t < 2 ? 640 + 640 * t : 0) + 80 * g; c1 = c0 + 64; bytes = 12800; }
          else if (t == 6) { c0 = c1 = 1536 + 48 * p; m0 = &M.w1c; m1 = &M.w3c; }
          else {
            c0 = c1 = 96 * (4 * (t - 2 & ~1) + g);
            if (t & 1) { m0 = &M.w3a; m1 = &M.w1b; c0 += 32; c1 += 64; } else { m0 = &M.w1a; m1 = &M.w3b; }
          }
          #pragma unroll 1
          for (int st = w; st < 8; st += 2) {
            const int it = 8 * t + st;
            if (it == 3) {
              #pragma unroll 1
              for (int i = 0; i < 5; i++) { mbar_expect(bars + 8 * (B_XFULL + 5 + i), 16384); tma3d(base + 7 * SLOT + i * 16384, &M.x, 0, rb * 128 + 64, 2 * i, bars + 8 * (B_XFULL + 5 + i)); }
            }
            if (it >= 3 && it < 9) mbar_wait(bars + 8 * (B_XFREE + (it >= 7)), 0);
            acquire(bytes);
            tma2d(dst, m0, c0, 80 * st, fb);
            tma2d(dst + 10240, m1, c1, 80 * st, fb);
          }
          if (t == 1) acquire(0);
        }
        PROFT(40 + 8 * w);
        const int k0 = role ? 0 : NY, k1 = role ? NY : 108;
        if (w == 0) {
          #pragma unroll 1
          for (int k = k0; k < k1; k += 4) {
            acquire(20480);
            tma2d(dst, &M.w2a, cl, 16 * k, fb);
            tma2d(dst + 8192, &M.w2a, cl + 64, 16 * k, fb);
            tma2d(dst + 16384, &M.w2b, ch, 16 * k, fb);
            PROFT(188 + (k - k0) / 4);
          }
          #pragma unroll 1
          for (int m = 0; m < 8; m++) {
            acquire(12800);
            tma2d(dst, &M.woa, cl + 64 * role, 80 * m, fb);
            tma2d(dst + 10240, &M.wob, ch + 16 * role, 80 * m, fb);
            PROFT(208 + m);
          }
        } else {
          unsigned ep1;
          asm volatile("ld.shared.u32 %0, [%1];" : "=r"(ep1) : "r"(base + OFF_EP) : "memory");
          ep1 += 1;
          #pragma unroll 1
          for (int k = k0; k < k1; k += 4) {
            const int n = min(4, k1 - k);
            if (k == k0 || k == (role ? 32 : NY + 16)) poll_ge(&g_cnt[(C_H + rb * 3 + (k == k0 ? 1 : 2) - role) * 8], ep1 * (k == NY + 16 ? 8 : 16));
            acquire(n * 4096);
            bulk(dst, g_h + (rb * 108 + k) * 256, n * 4096, fb);
            PROFT(168 + (k - k0) / 4);
          }
          PROFT(49);
          poll_ge(&g_cnt[(C_O + rb) * 8], ep1 * 16);
          PROFT(50);
          #pragma unroll 1
          for (int m = 0; m < 8; m++) {
            acquire(20480);
            bulk(dst, g_o + (rb * 40 + 5 * m) * 256, 20480, fb);
            PROFT(216 + m);
          }
        }
      }
    PROFEND();
    return;
  }
CONSUMER:
  {
    asm volatile("setmaxnreg.inc.sync.aligned.u32 240;");
    const int wg = warp >> 2, w4 = warp & 3, lane = tid & 31;
    const bool lane0 = lane == 0;
    uint32_t a[160];
    float r0, r1;
    {
      const int row = w4 * 16 + (lane & 15);
      const uint32_t xa = base + (wg ? 7 : 3) * SLOT + row * 128;
      float st[2][4];
      #pragma unroll
      for (int i = 0; i < 8; i++) st[i >> 2][i & 3] = 0.f;
      #pragma unroll
      for (int i = 0; i < 10; i++) {
        if (i == 0) PROFC(32 + wg * 4);
        if (!(i & 1)) mbar_wait(bars + 8 * (B_XFULL + wg * 5 + (i >> 1)), 0);
        if (i == 0) PROFC(33 + wg * 4);
        if (i == 8) PROFC(34 + wg * 4);
        #pragma unroll
        for (int j = 0; j < 4; j++) {
          const int k = 16 * i + 4 * j;
          asm volatile("ldmatrix.sync.aligned.m8n8.x4.shared.b16 {%0,%1,%2,%3}, [%4];" : "=r"(a[k]), "=r"(a[k + 1]), "=r"(a[k + 2]), "=r"(a[k + 3])
                       : "r"(xa + i * 8192 + (((2 * j + (lane >> 4)) ^ (row & 7)) << 4)) : "memory");
        }
        #pragma unroll
        for (int j = 0; j < 4; j++) { const int k = 16 * i + 4 * j; rowsum(st[j & 1], a[k], a[k + 1], a[k + 2], a[k + 3]); }
      }
      const float m0 = (st[0][0] + st[1][0]) * (1.f / 640), m1 = (st[0][2] + st[1][2]) * (1.f / 640);
      const uint32_t b0 = pack(m0, m0), b1 = pack(m1, m1);
      if (lane0) mbar_arrive(bars + 8 * (B_XFREE + wg) + (b0 & blockIdx.y));
      PROFC(35 + wg * 4);
      float q0 = 0.f, q1 = 0.f;
      #pragma unroll
      for (int k = 0; k < 160; k += 20) {
        #pragma unroll
        for (int j = 0; j < 20; j++) asm("sub.rn.bf16x2 %0, %0, %1;" : "+r"(a[k + j]) : "r"((j & 1) ? b1 : b0));
        uint32_t u0 = hmul(a[k], a[k]), u1 = hmul(a[k + 1], a[k + 1]);
        #pragma unroll
        for (int j = 2; j < 20; j += 2) { u0 = hfma(a[k + j], a[k + j], u0); u1 = hfma(a[k + j + 1], a[k + j + 1], u1); }
        q0 += blo(u0) + bhi(u0); q1 += blo(u1) + bhi(u1);
      }
      q0 += __shfl_xor_sync(0xffffffffu, q0, 1); q1 += __shfl_xor_sync(0xffffffffu, q1, 1);
      q0 += __shfl_xor_sync(0xffffffffu, q0, 2); q1 += __shfl_xor_sync(0xffffffffu, q1, 2);
      const float e0 = m0 - blo(b0), e1 = m1 - blo(b1);
      r0 = rsqrtf(fmaxf(fmaf(-e0, e0, q0 * (1.f / 640)), 0.f) + 1e-5f);
      r1 = rsqrtf(fmaxf(fmaf(-e1, e1, q1 * (1.f / 640)), 0.f) + 1e-5f);
    }
    PROFL(1 + wg * 16);
    float acc[48];
    const uint32_t evb = bars + 8 * (B_EV + wg * 5);
    #pragma unroll 1
    for (int tv = 0;; tv++) {
      const int t = __shfl_sync(0xffffffffu, tv, 0);
      PROFL(64 + wg * 16 + t);
      if (wg || t) asm volatile("bar.sync %0, 256;" :: "r"(4 - wg) : "memory");
      if (t < 2 || t == nt - 1) {
        tile_mma<80>(acc, a, t, base, lane0, 3 + wg);
        if (t >= 2) break;
        PROFC(2 + t + wg * 16);
        asm volatile("" : "+f"(r0), "+f"(r1));
        const int lane = fresh_tid() & 31, t4 = lane & 3;
        const int row = w4 * 16 + (lane & 15);
        const uint32_t so = row * 32 + ((((lane >> 4) ^ (row >> 2)) & 1) << 4);
        const uint32_t PK = base + OFF_AUX + wg * 10240;
        if (t == 0) {
          const float k0 = r0 * LOG2E, k1 = r1 * LOG2E;
          mbar_wait(bars + 8 * (B_XFREE + 1), 0);
          #pragma unroll
          for (int i = 0; i < 5; i++)
            stsm4(PK + so + i * 2048, phi2(acc[8 * i], acc[8 * i + 1], r0, k0), phi2(acc[8 * i + 2], acc[8 * i + 3], r1, k1),
                  phi2(acc[8 * i + 4], acc[8 * i + 5], r0, k0), phi2(acc[8 * i + 6], acc[8 * i + 7], r1, k1));
          continue;
        }
        mbar_wait(bars + 8 * 6, 1);
        mbar_wait(bars + 8 * 7, 1);
        if (lane0) mbar_arrive(bars + 8 * (B_EMPTY + 7 - wg));
        const uint32_t VS = base + (6 + wg) * SLOT;
        {
          uint32_t v[20];
          #pragma unroll
          for (int i = 0; i < 20; i++) { const float rr = (i & 1) ? r1 : r0; v[i] = pack(acc[2 * i] * rr, acc[2 * i + 1] * rr); }
          const uint32_t one = t4 == 0 ? 0x00003f80u : 0u;
          stsm4(VS + so, v[0], v[1], v[2], v[3]); stsm4(VS + so + 2048, v[4], v[5], v[6], v[7]); stsm4(VS + so + 4096, v[8], v[9], one, one);
          stsm4(VS + so + 6144, v[10], v[11], v[12], v[13]); stsm4(VS + so + 8192, v[14], v[15], v[16], v[17]); stsm4(VS + so + 10240, v[18], v[19], one, one);
        }
        asm volatile("fence.proxy.async.shared::cta;" ::: "memory");
        asm volatile("bar.sync %0, 128;" :: "r"(1 + wg) : "memory");
        const uint32_t al = (PK >> 4) | (128u << 16), bl = (VS >> 4) | (128u << 16);
        wg_fence();
        ss48tt<0, HI32, 0>(acc, al, bl); ss48tt<24, HI32, 0>(acc, al + 256, bl + 384);
        #pragma unroll
        for (int kk = 1; kk < 4; kk++) { ss48tt<0, HI32, 1>(acc, al + 32 * kk, bl + 32 * kk); ss48tt<24, HI32, 1>(acc, al + 256 + 32 * kk, bl + 384 + 32 * kk); }
        wg_commit();
        const int m0 = w4 * 16 + (lane >> 2);
        const uint32_t dst = VS + 12288 + m0 * 96 + t4 * 8;
        wg_wait<0>();
        pin<0, 48>(acc);
        #pragma unroll
        for (int i = 0; i < 4; i++) {
          const int j = i >> 1, hf = i & 1;
          const uint32_t d = m0 + 8 * hf - 8 * j;
          const int off = d >= 20 ? 20 : 0;
          const uint32_t dr = dst + (j * 40 + 8 * hf - 8 * j) * 96;
          const uint32_t e0 = d < 40 ? (uint32_t)(2 * t4 - off) : 1000u;
          #pragma unroll
          for (int jb = 0; jb < 5; jb++)
            asm volatile("{\n.reg .pred p;\nsetp.lt.u32 p, %0, 20;\n@p st.shared.v2.f32 [%1], {%2, %3};\n}"
                         :: "r"(e0 + 8 * jb), "r"(dr - off * 4 + 32 * jb), "f"(acc[24 * j + 4 * jb + 2 * hf]), "f"(acc[24 * j + 4 * jb + 2 * hf + 1]) : "memory");
          asm volatile("{\n.reg .pred p;\nsetp.lt.u32 p, %0, 2;\n@p st.shared.v2.f32 [%1], {%2, %3};\n}"
                       :: "r"((d < 40 ? 0 : 4) + t4), "r"(dr + 80), "f"(acc[24 * j + 20 + 2 * hf]), "f"(acc[24 * j + 21 + 2 * hf]) : "memory");
        }
        asm volatile("fence.proxy.async.shared::cta;" ::: "memory");
        __syncwarp();
        if (lane0) mbar_arrive(evb);
        PROFC(15 + wg * 16);
        continue;
      }
      if (t == 6) {
        tile_mma<48>(acc, a, t, base, lane0, 3 + wg);
        PROFC(2 + t + wg * 16);
        asm volatile("" : "+f"(r0), "+f"(r1));
        const float k0 = 0.5f * r0, k1 = 0.5f * r1;
        uint4* dst = g_h + (rb * 108 + 96 + 3 * p) * 256 + fresh_tid();
        #pragma unroll
        for (int s = 0; s < 3; s++) {
          uint32_t h[4];
          #pragma unroll
          for (int c = 0; c < 4; c++) {
            const int o = 8 * s + 2 * c; const float rr = (c & 1) ? r1 : r0, kk = (c & 1) ? k1 : k0;
            h[c] = pack(silu2(acc[o] * kk) * (acc[24 + o] * rr), silu2(acc[o + 1] * kk) * (acc[25 + o] * rr));
          }
          dst[s * 256] = make_uint4(h[0], h[1], h[2], h[3]);
        }
        __syncwarp();
        if (lane0) mbar_arrive(evb + 8 * 3);
        continue;
      }
      tile_mma<96>(acc, a, t, base, lane0, 3 + wg);
      PROFC(2 + t + wg * 16);
      asm volatile("" : "+f"(r0), "+f"(r1));
      const int tid = fresh_tid();
      const float k0 = 0.5f * r0, k1 = 0.5f * r1;
      const uint32_t stash = base + OFF_AUX + 20480 - wg * 4096 + (tid & 127) * 16;
      uint4* dst = g_h + (rb * 108 + 6 * (4 * (t - 2 & ~1) + g)) * 256 + tid;
      if (!(t & 1)) {
        #pragma unroll
        for (int s = 0; s < 4; s++) {
          uint32_t h[4];
          #pragma unroll
          for (int c = 0; c < 4; c++) {
            const int o = 8 * s + 2 * c; const float rr = (c & 1) ? r1 : r0, kk = (c & 1) ? k1 : k0;
            h[c] = s < 2 ? pack(silu2(acc[o] * kk) * (acc[32 + o] * rr), silu2(acc[o + 1] * kk) * (acc[33 + o] * rr)) : pack(silu2(acc[o] * kk), silu2(acc[o + 1] * kk));
          }
          if (s < 2) dst[s * 256] = make_uint4(h[0], h[1], h[2], h[3]); else sts128(stash + (s - 2) * 2048, h[0], h[1], h[2], h[3]);
        }
        continue;
      }
      #pragma unroll
      for (int s = 0; s < 4; s++) {
        uint32_t h[4];
        if (s < 2) {
          const uint4 u = lds128(stash + s * 2048);
          h[0] = pack(blo(u.x) * (acc[8 * s] * r0), bhi(u.x) * (acc[8 * s + 1] * r0)); h[1] = pack(blo(u.y) * (acc[8 * s + 2] * r1), bhi(u.y) * (acc[8 * s + 3] * r1));
          h[2] = pack(blo(u.z) * (acc[8 * s + 4] * r0), bhi(u.z) * (acc[8 * s + 5] * r0)); h[3] = pack(blo(u.w) * (acc[8 * s + 6] * r1), bhi(u.w) * (acc[8 * s + 7] * r1));
        } else {
          #pragma unroll
          for (int c = 0; c < 4; c++) {
            const int o = 8 * s + 2 * c; const float rr = (c & 1) ? r1 : r0, kk = (c & 1) ? k1 : k0;
            h[c] = pack(silu2(acc[16 + o] * kk) * (acc[o] * rr), silu2(acc[17 + o] * kk) * (acc[o + 1] * rr));
          }
        }
        dst[(2 + s) * 256] = make_uint4(h[0], h[1], h[2], h[3]);
      }
      __syncwarp();
      if (lane0) mbar_arrive(evb + 8 * (t >> 1));
    }
    {
      PROFC(9 + wg * 16);
      const int t4 = lane & 3;
      const float k0 = r0 * LOG2E, k1 = r1 * LOG2E;
      uint32_t q[20];
      #pragma unroll
      for (int i = 0; i < 20; i++) q[i] = phi2(acc[2 * i], acc[2 * i + 1], (i & 1) ? r1 : r0, (i & 1) ? k1 : k0);
      mbar_wait(bars + 8 * B_KVRDY, 0);
      uint64_t db = desc(((base + OFF_AUX) >> 4) | (1u << 16), HI32);
      wg_fence();
      rs88k<0, 0>(acc, q[0], q[1], q[2], q[3], db, 176);
      #pragma unroll
      for (int s = 1; s < 5; s++) rs88k<0, 1>(acc, q[4 * s], q[4 * s + 1], q[4 * s + 2], q[4 * s + 3], db, 176);
      wg_commit();
      wg_wait<0>();
      pin<0, 44>(acc);
      float dn[2][4];
      #pragma unroll
      for (int hf = 0; hf < 2; hf++) {
        const float u = rcp(acc[40 + 2 * hf] + 1e-6f), v = rcp(acc[41 + 2 * hf] + 1e-6f);
        dn[hf][0] = __shfl_sync(0xffffffffu, u, lane & 28); dn[hf][1] = __shfl_sync(0xffffffffu, v, lane & 28);
        dn[hf][2] = __shfl_sync(0xffffffffu, u, (lane & 28) + 1); dn[hf][3] = __shfl_sync(0xffffffffu, v, (lane & 28) + 1);
      }
      uint4* dst = g_o + (rb * 40 + 5 * g) * 256 + tid;
      #pragma unroll
      for (int s = 0; s < 5; s++) {
        uint32_t o[4];
        #pragma unroll
        for (int c = 0; c < 4; c++) {
          const int blk = 2 * s + (c >> 1), hf = c & 1;
          const float sc = blk == 2 ? (t4 < 2 ? dn[hf][0] : dn[hf][1]) : blk == 7 ? (t4 < 2 ? dn[hf][2] : dn[hf][3]) : dn[hf][(8 * blk) / 20];
          o[c] = pack(acc[4 * blk + 2 * hf] * sc, acc[4 * blk + 2 * hf + 1] * sc);
        }
        dst[s * 256] = make_uint4(o[0], o[1], o[2], o[3]);
      }
      __syncwarp();
      if (lane0) mbar_arrive(evb + 8 * (nt - 4));
      PROFL(10 + wg * 16);
    }
    if (!wg) asm volatile("bar.sync 4, 256;" ::: "memory");
    {
      float c1[64], c2[16], c[40], keep[40];
      uint4 fa[3][5], xv[5], pv[5];
      Ring r;
      r.at(8 * nt + 2, base);
      uint32_t prev = 0;
      int sidx = 0;
      auto stage = [&](uint4 (&f)[5], int nk, uint4 (&fn)[5], int nn, bool fetch, bool rela, bool relb, auto issue, auto extra) {
        Ring n = r; n.next<2>(bars);
        if (lane0 && rela) mbar_arrive(r.fb + 88 + (f[nk - 1].w & blockIdx.y));
        if (fetch) mbar_wait(n.fb + 8, n.ph);
        #pragma unroll
        for (int kk = 0; kk < 5; kk++) if (kk < nn) fn[kk] = lds128((n.lo << 4) + SLOT + kk * 4096 + tid * 16);
        wg_fence();
        issue(r.lo);
        wg_commit();
        extra();
        if (fetch) mbar_wait(n.fb, n.ph);
        wg_wait<1>();
        if (lane0 && relb) mbar_arrive(prev + 80);
        prev = r.fb;
        r = n;
      };
      auto down = [&](uint4 (&f)[5], int nk, uint4 (&fn)[5], int nn, bool relb) {
        stage(f, nk, fn, nn, true, true, relb, [&](uint32_t lo) {
          uint64_t d1 = desc(lo | (512u << 16), HI128), d2 = desc(lo + 1024, HI64);
          #pragma unroll
          for (int kk = 0; kk < 4; kk++) if (kk < nk) {
            rs128<0, 1>(c1, f[kk].x, f[kk].y, f[kk].z, f[kk].w, d1, 128);
            rs32<0, 1>(c2, f[kk].x, f[kk].y, f[kk].z, f[kk].w, d2, 64);
          }
        }, [] {});
      };
      auto outp = [&](uint4 (&f)[5], uint4 (&fn)[5], bool first, bool fetch, bool rela, bool relb, auto extra) {
        PROFL(224 + wg * 10 + sidx); sidx++;
        stage(f, 5, fn, 5, fetch, rela, relb, [&](uint32_t lo) {
          uint64_t db = desc(lo | (640u << 16), HI128);
          if (first) rs80<0, 0>(c, f[0].x, f[0].y, f[0].z, f[0].w, db, 128); else rs80<0, 1>(c, f[0].x, f[0].y, f[0].z, f[0].w, db, 128);
          #pragma unroll
          for (int kk = 1; kk < 5; kk++) rs80<0, 1>(c, f[kk].x, f[kk].y, f[kk].z, f[kk].w, db, 128);
        }, extra);
      };
      uint32_t go[5];
      #pragma unroll
      for (int i = 0; i < 5; i++) {
        const int ci = lane + 32 * i, rw = ci / 10;
        const int cc = ci - rw * 10;
        go[i] = (rb * 128 + warp * 16 + rw) * D_ + (cc < 8 ? cl + 64 * role : ch + 16 * role - 64) + cc * 8;
        xv[i] = __ldg(reinterpret_cast<const uint4*>(x + go[i]));
      }
      mbar_wait(r.fb + 8, r.ph);
      #pragma unroll
      for (int kk = 0; kk < 4; kk++) fa[0][kk] = lds128((r.lo << 4) + SLOT + kk * 4096 + tid * 16);
      #pragma unroll
      for (int i = 0; i < 64; i++) c1[i] = 0.f;
      #pragma unroll
      for (int i = 0; i < 16; i++) c2[i] = 0.f;
      pin<0, 64>(c1); pin<0, 16>(c2);
      mbar_wait(r.fb, r.ph);
      const int ntrip = role ? 5 : 3;
      #pragma unroll 1
      for (int m = 0;; m++) {
        PROFL(128 + wg * 20 + 3 * m);
        down(fa[0], 4, fa[1], 4, m > 0);
        if (m == ntrip) break;
        PROFC(129 + wg * 20 + 3 * m);
        down(fa[1], 4, fa[2], 4, true);
        PROFC(130 + wg * 20 + 3 * m);
        down(fa[2], 4, fa[0], 4, true);
      }
      PROFC(129 + wg * 20 + 3 * ntrip);
      down(fa[1], 2, fa[2], 5, true);
      uint32_t tag;
      asm volatile("ld.shared.u32 %0, [%1];" : "=r"(tag) : "r"(base + OFF_EP) : "memory");
      tag = (tag + 1) & 1;
      outp(fa[2], fa[0], true, true, true, true, [] {});
      pin<0, 64>(c1); pin<0, 16>(c2);
      PROFC(11 + wg * 16);
      outp(fa[0], fa[1], false, true, true, true, [&] {
        uint4* dst = g_p + (b * 8 + warp) * 160 + lane;
        auto put = [&](int i, const float* v) { stg_relaxed(dst + i * 32, (pack(v[0], v[1]) & ~1u) | tag, pack(v[2], v[3]), pack(v[4], v[5]), pack(v[6], v[7])); };
        if (role == 0) {
          #pragma unroll
          for (int i = 0; i < 5; i++) put(i, i < 4 ? &c1[32 + 8 * i] : &c2[8]);
          #pragma unroll
          for (int i = 0; i < 40; i++) keep[i] = i < 32 ? c1[i] : c2[i - 32];
        } else {
          #pragma unroll
          for (int i = 0; i < 5; i++) put(i, i < 4 ? &c1[8 * i] : &c2[0]);
          #pragma unroll
          for (int i = 0; i < 40; i++) keep[i] = i < 32 ? c1[32 + i] : c2[i - 24];
        }
        pin<0, 40>(keep);
      });
      const uint4* src = g_p + ((b ^ 64) * 8 + warp) * 160 + lane;
      auto gate = [&](int i0, int i1) {
        #pragma unroll
        for (int i = i0; i < i1; i++) {
          const uint4 v = pv[i / 8]; const int j = (i >> 1) & 3; const uint32_t u = j == 0 ? v.x : j == 1 ? v.y : j == 2 ? v.z : v.w;
          keep[i] = silu2(0.5f * (keep[i] + ((i & 1) ? bhi(u) : blo(u))));
          asm volatile("" : "+f"(keep[i]));
        }
      };
      #pragma unroll
      for (int i = 0; i < 5; i++) pv[i] = make_uint4(0, 0, 0, 0);
      #pragma unroll 1
      for (int m = 0; m < 2; m++) {
        outp(fa[1], fa[2], false, true, m == 0, m == 0, [] {});
        outp(fa[2], fa[0], false, true, false, m == 0, [&] {
          if (m) {
            uint32_t bad = 0, n = 0;
            #pragma unroll 1
            do {
              #pragma unroll
              for (int i = 0; i < 5; i++)
                asm volatile("{\n.reg .pred p;\nsetp.ne.u32 p, %5, 0;\n@p ld.relaxed.gpu.global.v4.u32 {%0, %1, %2, %3}, [%4];\n}"
                             : "+r"(pv[i].x), "+r"(pv[i].y), "+r"(pv[i].z), "+r"(pv[i].w) : "l"(src + i * 32), "r"(bad) : "memory");
              bad = 0;
              #pragma unroll
              for (int i = 0; i < 5; i++) bad |= pv[i].x ^ tag;
              bad = __any_sync(0xffffffffu, bad & 1);
            } while (bad && ++n < (1u << 18));
            PROFL(12 + wg * 16);
            gate(0, 16);
          }
        });
        outp(fa[0], fa[1], false, m == 0, false, false, [&] {
          if (m) gate(16, 40);
          else {
            #pragma unroll
            for (int i = 0; i < 5; i++) pv[i] = ldg_relaxed(src + i * 32);
          }
        });
      }
      wg_wait<0>();
      pin<0, 40>(c);
      PROFL(13 + wg * 16);
      const uint32_t yb = base + OFF_AUX + warp * 2816;
      #pragma unroll
      for (int i = 0; i < 5; i++)
        stsm4(yb + (lane & 15) * 176 + (lane >> 4) * 16 + i * 32, pack(c[8 * i] * keep[8 * i], c[8 * i + 1] * keep[8 * i + 1]), pack(c[8 * i + 2] * keep[8 * i + 2], c[8 * i + 3] * keep[8 * i + 3]),
              pack(c[8 * i + 4] * keep[8 * i + 4], c[8 * i + 5] * keep[8 * i + 5]), pack(c[8 * i + 6] * keep[8 * i + 6], c[8 * i + 7] * keep[8 * i + 7]));
      __syncwarp();
      #pragma unroll
      for (int i = 0; i < 5; i++) {
        const int ci = lane + 32 * i, rw = ci / 10;
        uint4 y = lds128(yb + ci * 16 + rw * 16);
        asm("add.rn.bf16x2 %0, %0, %1;" : "+r"(y.x) : "r"(xv[i].x)); asm("add.rn.bf16x2 %0, %0, %1;" : "+r"(y.y) : "r"(xv[i].y));
        asm("add.rn.bf16x2 %0, %0, %1;" : "+r"(y.z) : "r"(xv[i].z)); asm("add.rn.bf16x2 %0, %0, %1;" : "+r"(y.w) : "r"(xv[i].w));
        *reinterpret_cast<uint4*>(out + go[i]) = y;
      }
      PROFL(14 + wg * 16);
    }
    PROFEND();
    if (blockIdx.y == 0) return;
  }
PUBLISHER:
  {
    const int lane = tid & 31;
      const int w = warp - 10, nev = role ? 4 : 5;
      unsigned ep = 0;
      if (lane == 0) {
        if (w) {
          ep = *(volatile unsigned*)&g_epoch[b];
          *(volatile unsigned*)&g_epoch[b] = ep + 1;
          asm volatile("st.shared.u32 [%0], %1;" :: "r"(base + OFF_EP), "r"(ep) : "memory");
          mbar_arrive(bars + 8 * B_EP);
        } else {
          mbar_wait(bars + 8 * B_EP, 0);
          asm volatile("ld.shared.u32 %0, [%1];" : "=r"(ep) : "r"(base + OFF_EP) : "memory");
        }
      }
      ep = __shfl_sync(0xffffffffu, ep, 0);
      if (w && lane < 30) reinterpret_cast<float4*>(g_kv + ((ep + 1) & 1) * 15360 + b * 120)[lane] = make_float4(0.f, 0.f, 0.f, 0.f);
      const float* kvs = g_kv + ((ep & 1) * 8 + g) * 1920;
      if (elect()) {
        mbar_wait(bars + 8 * (B_EV + w * 5), 0);
        asm volatile("cp.reduce.async.bulk.global.shared::cta.bulk_group.add.f32 [%0], [%1], 7680;" :: "l"(kvs), "r"(base + (6 + w) * SLOT + 12288) : "memory");
        asm volatile("cp.async.bulk.commit_group;" ::: "memory");
        asm volatile("cp.async.bulk.wait_group.read 0;" ::: "memory");
        asm volatile("mbarrier.arrive.shared::cta.b64 _, [%0], 4;" :: "r"(bars + 8 * (B_EMPTY + 6 + w)) : "memory");
        asm volatile("cp.async.bulk.wait_group 0;" ::: "memory");
        asm volatile("fence.proxy.async.global;" ::: "memory");
        asm volatile("red.release.gpu.global.add.u32 [%0], 1;" :: "l"(&g_cnt[(C_KV + g) * 8]) : "memory");
        if (w) PROFT(52);
        poll_ge(&g_cnt[(C_KV + g) * 8], (ep + 1) * 32);
        if (w) PROFT(53);
      }
      __syncwarp();
      {
        const uint32_t kb = base + OFF_AUX;
        const int eq = lane % 6, dpo = lane / 6;
        #pragma unroll 1
        for (int i = lane + 32 * w; i < 880; i += 64) sts128(kb + i * 16, 0, 0, 0, 0);
        asm volatile("bar.sync 5, 64;" ::: "memory");
        if (lane < 30) {
          #pragma unroll 1
          for (int i = 4 * w; i < 4 * w + 4; i++) {
            const int h = i >> 1, d = 10 * i + 2 * dpo, n = eq < 5 ? 20 * h + 4 * eq : 80 + h;
            const uint4 u = ldg_relaxed(kvs + d * 24 + eq * 4), v = ldg_relaxed(kvs + d * 24 + 24 + eq * 4);
            const uint32_t ad = kb + (d >> 4) * 2816 + n * 32 + ((((d >> 3) ^ (n >> 2)) & 1) << 4) + (d & 7) * 2;
            asm volatile("st.shared.u32 [%0], %1;" :: "r"(ad), "r"(pack(__uint_as_float(u.x), __uint_as_float(v.x))) : "memory");
            if (eq < 5) {
              asm volatile("st.shared.u32 [%0], %1;" :: "r"(ad + 32), "r"(pack(__uint_as_float(u.y), __uint_as_float(v.y))) : "memory");
              asm volatile("st.shared.u32 [%0], %1;" :: "r"(ad + 64), "r"(pack(__uint_as_float(u.z), __uint_as_float(v.z))) : "memory");
              asm volatile("st.shared.u32 [%0], %1;" :: "r"(ad + 96), "r"(pack(__uint_as_float(u.w), __uint_as_float(v.w))) : "memory");
            }
          }
        }
        asm volatile("fence.proxy.async.shared::cta;" ::: "memory");
        __syncwarp();
        if (lane == 0) { mbar_arrive(bars + 8 * B_KVRDY); if (w) PROFT(46); }
      }
      if (lane == 0) {
        #pragma unroll 1
        for (int e = 1; e < nev; e++) {
          const int c = e == nev - 1 ? C_O + rb : C_H + rb * 3 + (e - 1);
          mbar_wait(bars + 8 * (B_EV + w * 5 + e), 0);
          asm volatile("red.release.gpu.global.add.u32 [%0], 1;" :: "l"(&g_cnt[c * 8]) : "memory");
        }
      }
    PROFEND();
  }
}

typedef CUresult (*EncFn)(CUtensorMap*, CUtensorMapDataType, cuuint32_t, void*, const cuuint64_t*, const cuuint64_t*, const cuuint32_t*,
                          const cuuint32_t*, CUtensorMapInterleave, CUtensorMapSwizzle, CUtensorMapL2promotion, CUtensorMapFloatOOBfill);

CUtensorMap make_map(EncFn enc, const void* p, int rows, int cols, int box_r, int box_c, CUtensorMapSwizzle swz) {
  CUtensorMap m;
  cuuint64_t dims[2] = {(cuuint64_t)cols, (cuuint64_t)rows};
  cuuint64_t str[1] = {(cuuint64_t)cols * 2};
  cuuint32_t box[2] = {(cuuint32_t)box_c, (cuuint32_t)box_r};
  cuuint32_t es[2] = {1, 1};
  enc(&m, CU_TENSOR_MAP_DATA_TYPE_BFLOAT16, 2, const_cast<void*>(p), dims, str, box, es, CU_TENSOR_MAP_INTERLEAVE_NONE, swz,
      CU_TENSOR_MAP_L2_PROMOTION_L2_128B, CU_TENSOR_MAP_FLOAT_OOB_FILL_NONE);
  return m;
}

}

extern "C" void kernel_launch(void* const* d_in, const int* in_sizes, int n_in, void* d_out, int out_size) {
  (void)in_sizes; (void)n_in; (void)out_size;
  static EncFn enc = nullptr;
  if (!enc) {
    cudaDriverEntryPointQueryResult q;
    cudaGetDriverEntryPoint("cuTensorMapEncodeTiled", (void**)&enc, cudaEnableDefault, &q);
    cudaFuncSetAttribute(fused_kernel, cudaFuncAttributeMaxDynamicSharedMemorySize, SMEM_BYTES);
  }
  Maps M;
  {
    cuuint64_t dims[3] = {64, (cuuint64_t)S_, 10}, str[2] = {D_ * 2, 128};
    cuuint32_t box[3] = {64, 64, 2}, es[3] = {1, 1, 1};
    enc(&M.x, CU_TENSOR_MAP_DATA_TYPE_BFLOAT16, 3, d_in[0], dims, str, box, es, CU_TENSOR_MAP_INTERLEAVE_NONE, CU_TENSOR_MAP_SWIZZLE_128B,
        CU_TENSOR_MAP_L2_PROMOTION_L2_128B, CU_TENSOR_MAP_FLOAT_OOB_FILL_NONE);
  }
  M.qkv64 = make_map(enc, d_in[1], D_, 3 * D_, 80, 64, CU_TENSOR_MAP_SWIZZLE_128B);
  M.qkv16 = make_map(enc, d_in[1], D_, 3 * D_, 80, 16, CU_TENSOR_MAP_SWIZZLE_128B);
  M.woa = make_map(enc, d_in[2], D_, D_, 80, 64, CU_TENSOR_MAP_SWIZZLE_128B);
  M.wob = make_map(enc, d_in[2], D_, D_, 80, 16, CU_TENSOR_MAP_SWIZZLE_128B);
  M.w1a = make_map(enc, d_in[4], D_, F_, 80, 64, CU_TENSOR_MAP_SWIZZLE_128B);
  M.w1b = make_map(enc, d_in[4], D_, F_, 80, 32, CU_TENSOR_MAP_SWIZZLE_128B);
  M.w3a = make_map(enc, d_in[5], D_, F_, 80, 64, CU_TENSOR_MAP_SWIZZLE_128B);
  M.w3b = make_map(enc, d_in[5], D_, F_, 80, 32, CU_TENSOR_MAP_SWIZZLE_128B);
  M.w1c = make_map(enc, d_in[4], D_, F_, 80, 48, CU_TENSOR_MAP_SWIZZLE_128B);
  M.w3c = make_map(enc, d_in[5], D_, F_, 80, 48, CU_TENSOR_MAP_SWIZZLE_128B);
  M.w2a = make_map(enc, d_in[6], F_, D_, 64, 64, CU_TENSOR_MAP_SWIZZLE_128B);
  M.w2b = make_map(enc, d_in[6], F_, D_, 64, 32, CU_TENSOR_MAP_SWIZZLE_64B);
  fused_kernel<<<128, 384, SMEM_BYTES>>>(M, (const __nv_bfloat16*)d_in[0], (__nv_bfloat16*)d_out);
}
```

```cpp
#include <cuda_runtime.h>
#include <cuda_bf16.h>
#include <cuda.h>
#include <stdint.h>

namespace {

constexpr int S_ = 2048, D_ = 640, F_ = 1728;
constexpr int NSLOT = 10, SLOT = 20480;
constexpr int OFF_AUX = NSLOT * SLOT;
constexpr int OFF_BAR = OFF_AUX + 24576;
constexpr int B_EMPTY = 10, B_XFULL = 20, B_XFREE = 30, B_EV = 33, B_KVRDY = 43, B_EP = 44, B_XRES = 45, B_AUXF = 46, B_OK = 47;
constexpr int OFF_EP = OFF_BAR + 58 * 8;
constexpr int OFF_PROF = OFF_EP + 16;
constexpr int SMEM_BYTES = OFF_PROF + 1024;
#define S0 6
#define XLN 160
#define PRIO 1
#define DLY 20
#define S1 6
#define RV 5
#define MAP 3
constexpr int NY = 66;

__device__ uint4 g_h[16 * 108 * 256];
__device__ uint4 g_o[16 * 40 * 256];
__device__ uint4 g_p[128 * 8 * 5 * 32];
__device__ float g_kv[2 * 8 * 2 * 960];
__device__ unsigned g_cnt[128 * 8];
__device__ unsigned g_epoch[128];
constexpr int C_H = 0, C_O = 48, C_KV = 80;

#define PROFC(i)
#define PROFT(i)
#define PROFT_(i)
#define TWAIT(bar, ph, i) mbar_wait(bar, ph)
#define PROFL(i)
#define PROFEND()

__device__ __forceinline__ uint32_t smem_u32(const void* p) { return (uint32_t)__cvta_generic_to_shared(p); }
__device__ __forceinline__ void mbar_init(uint32_t bar, uint32_t cnt) { asm volatile("mbarrier.init.shared::cta.b64 [%0], %1;" :: "r"(bar), "r"(cnt) : "memory"); }
__device__ __forceinline__ void mbar_expect(uint32_t bar, uint32_t bytes) { asm volatile("mbarrier.arrive.expect_tx.shared::cta.b64 _, [%0], %1;" :: "r"(bar), "r"(bytes) : "memory"); }
__device__ __forceinline__ void mbar_arrive(uint32_t bar) { asm volatile("mbarrier.arrive.shared::cta.b64 _, [%0];" :: "r"(bar) : "memory"); }
__device__ __forceinline__ void mbar_wait(uint32_t bar, uint32_t parity) {
  asm volatile("{\n.reg .pred p;\nLOOP:\nmbarrier.try_wait.parity.shared::cta.b64 p, [%0], %1;\n@!p bra.uni LOOP;\n}" :: "r"(bar), "r"(parity) : "memory");
}
__device__ __forceinline__ void poll_ge(const unsigned* p, unsigned target) {
  #pragma unroll 1
  for (uint32_t n = 0; n < (1u << 20); n++) {
    unsigned v;
    asm volatile("ld.acquire.gpu.global.u32 %0, [%1];" : "=r"(v) : "l"(p) : "memory");
    if ((int)(v - target) >= 0) break;
  }
}
__device__ __forceinline__ void tma2d(uint32_t dst, const CUtensorMap* m, int c0, int c1, uint32_t bar) {
  asm volatile("cp.async.bulk.tensor.2d.shared::cluster.global.mbarrier::complete_tx::bytes [%0], [%1, {%3, %4}], [%2];"
    :: "r"(dst), "l"(m), "r"(bar), "r"(c0), "r"(c1) : "memory");
}
__device__ __forceinline__ void tma3d(uint32_t dst, const CUtensorMap* m, int c0, int c1, int c2, uint32_t bar) {
  asm volatile("cp.async.bulk.tensor.3d.shared::cluster.global.mbarrier::complete_tx::bytes [%0], [%1, {%3, %4, %5}], [%2];"
    :: "r"(dst), "l"(m), "r"(bar), "r"(c0), "r"(c1), "r"(c2) : "memory");
}
__device__ __forceinline__ void bulk(uint32_t dst, const void* src, uint32_t bytes, uint32_t bar) {
  asm volatile("cp.async.bulk.shared::cluster.global.mbarrier::complete_tx::bytes [%0], [%1], %2, [%3];" :: "r"(dst), "l"(src), "r"(bytes), "r"(bar) : "memory");
}
__device__ __forceinline__ void wg_fence() { asm volatile("wgmma.fence.sync.aligned;" ::: "memory"); }
__device__ __forceinline__ void wg_commit() { asm volatile("wgmma.commit_group.sync.aligned;" ::: "memory"); }
template<int N> __device__ __forceinline__ void wg_wait() { asm volatile("wgmma.wait_group.sync.aligned %0;" :: "n"(N) : "memory"); }
template<int O, int N, int L> __device__ __forceinline__ void pin(float (&d)[L]) {
  #pragma unroll
  for (int i = 0; i < N; i++) asm volatile("" : "+f"(d[O + i]) :: "memory");
}
__device__ __forceinline__ int fresh_tid() { int t; asm volatile("mov.u32 %0, %%tid.x;" : "=r"(t)); return t; }
__device__ __forceinline__ uint4 lds128(uint32_t a) { uint4 v; asm volatile("ld.shared.v4.u32 {%0,%1,%2,%3}, [%4];" : "=r"(v.x), "=r"(v.y), "=r"(v.z), "=r"(v.w) : "r"(a) : "memory"); return v; }
__device__ __forceinline__ uint4 ldg_relaxed(const void* p) {
  uint4 v;
  asm volatile("ld.relaxed.gpu.global.v4.u32 {%0, %1, %2, %3}, [%4];" : "=r"(v.x), "=r"(v.y), "=r"(v.z), "=r"(v.w) : "l"(p) : "memory");
  return v;
}
__device__ __forceinline__ void stg_relaxed(void* p, uint32_t x, uint32_t y, uint32_t z, uint32_t w) {
  asm volatile("st.relaxed.gpu.global.v4.u32 [%0], {%1, %2, %3, %4};" :: "l"(p), "r"(x), "r"(y), "r"(z), "r"(w) : "memory");
}
__device__ __forceinline__ void sts128(uint32_t a, uint32_t x, uint32_t y, uint32_t z, uint32_t w) {
  asm volatile("st.shared.v4.u32 [%0], {%1,%2,%3,%4};" :: "r"(a), "r"(x), "r"(y), "r"(z), "r"(w) : "memory");
}
__device__ __forceinline__ void stsm4(uint32_t a, uint32_t r0, uint32_t r1, uint32_t r2, uint32_t r3) {
  asm volatile("stmatrix.sync.aligned.m8n8.x4.shared.b16 [%0], {%1,%2,%3,%4};" :: "r"(a), "r"(r0), "r"(r1), "r"(r2), "r"(r3) : "memory");
}
__device__ __forceinline__ uint32_t pack(float lo, float hi) { uint32_t r; asm("cvt.rn.bf16x2.f32 %0, %1, %2;" : "=r"(r) : "f"(hi), "f"(lo)); return r; }
__device__ __forceinline__ float blo(uint32_t v) { return __uint_as_float(v << 16); }
__device__ __forceinline__ float bhi(uint32_t v) { return __uint_as_float(v & 0xffff0000u); }
__device__ __forceinline__ float ex2(float x) { float y; asm("ex2.approx.ftz.f32 %0, %1;" : "=f"(y) : "f"(x)); return y; }
__device__ __forceinline__ float rcp(float x) { float y; asm("rcp.approx.ftz.f32 %0, %1;" : "=f"(y) : "f"(x)); return y; }
__device__ __forceinline__ float tanh_(float x) { float y; asm("tanh.approx.f32 %0, %1;" : "=f"(y) : "f"(x)); return y; }
__device__ __forceinline__ uint32_t hadd(uint32_t a, uint32_t b) { uint32_t r; asm("add.rn.bf16x2 %0, %1, %2;" : "=r"(r) : "r"(a), "r"(b)); return r; }
__device__ __forceinline__ uint32_t hmul(uint32_t a, uint32_t b) { uint32_t r; asm("mul.rn.bf16x2 %0, %1, %2;" : "=r"(r) : "r"(a), "r"(b)); return r; }
__device__ __forceinline__ uint32_t hfma(uint32_t a, uint32_t b, uint32_t c) { uint32_t r; asm("fma.rn.bf16x2 %0, %1, %2, %3;" : "=r"(r) : "r"(a), "r"(b), "r"(c)); return r; }
__device__ __forceinline__ void rowsum(float (&d)[4], uint32_t a0, uint32_t a1, uint32_t a2, uint32_t a3) {
  asm volatile("mma.sync.aligned.m16n8k16.row.col.f32.bf16.bf16.f32 {%0,%1,%2,%3}, {%4,%5,%6,%7}, {%8,%8}, {%0,%1,%2,%3};"
               : "+f"(d[0]), "+f"(d[1]), "+f"(d[2]), "+f"(d[3]) : "r"(a0), "r"(a1), "r"(a2), "r"(a3), "r"(0x3f803f80u));
}
constexpr float LOG2E = 1.4426950408889634f;
template<int SCALED> __device__ __forceinline__ uint32_t phi2(float u, float v, float r, float k) {
  const float s = SCALED ? r : 1.f, e = 1e-6f * s;
  return pack(fmaf(u > 0.f ? fmaf(u, r, 1.f) : ex2(u * k), s, e), fmaf(v > 0.f ? fmaf(v, r, 1.f) : ex2(v * k), s, e));
}
__device__ __forceinline__ float silu2(float h) { return fmaf(h, tanh_(h), h); }

template<int O, int SD, int L> __device__ __forceinline__ void rs96(float (&d)[L], uint32_t a0, uint32_t a1, uint32_t a2, uint32_t a3, uint64_t& db, uint32_t st) {
  if (SD) asm volatile("{\n.reg .pred p;\nsetp.ne.b32 p, 1, 0;\n"
    "wgmma.mma_async.sync.aligned.m64n96k16.f32.bf16.bf16 {%0, %1, %2, %3, %4, %5, %6, %7, %8, %9, %10, %11, %12, %13, %14, %15, %16, %17, %18, %19, %20, %21, %22, %23, %24, %25, %26, %27, %28, %29, %30, %31, %32, %33, %34, %35, %36, %37, %38, %39, %40, %41, %42, %43, %44, %45, %46, %47}, {%48, %49, %50, %51}, %52, p, 1, 1, 1;\n}\n"
    : "+f"(d[O + 0]), "+f"(d[O + 1]), "+f"(d[O + 2]), "+f"(d[O + 3]), "+f"(d[O + 4]), "+f"(d[O + 5]), "+f"(d[O + 6]), "+f"(d[O + 7]), "+f"(d[O + 8]), "+f"(d[O + 9]), "+f"(d[O + 10]), "+f"(d[O + 11]), "+f"(d[O + 12]), "+f"(d[O + 13]), "+f"(d[O + 14]), "+f"(d[O + 15]), "+f"(d[O + 16]), "+f"(d[O + 17]), "+f"(d[O + 18]), "+f"(d[O + 19]), "+f"(d[O + 20]), "+f"(d[O + 21]), "+f"(d[O + 22]), "+f"(d[O + 23]), "+f"(d[O + 24]), "+f"(d[O + 25]), "+f"(d[O + 26]), "+f"(d[O + 27]), "+f"(d[O + 28]), "+f"(d[O + 29]), "+f"(d[O + 30]), "+f"(d[O + 31]), "+f"(d[O + 32]), "+f"(d[O + 33]), "+f"(d[O + 34]), "+f"(d[O + 35]), "+f"(d[O + 36]), "+f"(d[O + 37]), "+f"(d[O + 38]), "+f"(d[O + 39]), "+f"(d[O + 40]), "+f"(d[O + 41]), "+f"(d[O + 42]), "+f"(d[O + 43]), "+f"(d[O + 44]), "+f"(d[O + 45]), "+f"(d[O + 46]), "+f"(d[O + 47])
    : "r"(a0), "r"(a1), "r"(a2), "r"(a3), "l"(db));
  else asm volatile("{\n.reg .pred p;\nsetp.ne.b32 p, 0, 0;\n"
    "wgmma.mma_async.sync.aligned.m64n96k16.f32.bf16.bf16 {%0, %1, %2, %3, %4, %5, %6, %7, %8, %9, %10, %11, %12, %13, %14, %15, %16, %17, %18, %19, %20, %21, %22, %23, %24, %25, %26, %27, %28, %29, %30, %31, %32, %33, %34, %35, %36, %37, %38, %39, %40, %41, %42, %43, %44, %45, %46, %47}, {%48, %49, %50, %51}, %52, p, 1, 1, 1;\n}\n"
    : "=f"(d[O + 0]), "=f"(d[O + 1]), "=f"(d[O + 2]), "=f"(d[O + 3]), "=f"(d[O + 4]), "=f"(d[O + 5]), "=f"(d[O + 6]), "=f"(d[O + 7]), "=f"(d[O + 8]), "=f"(d[O + 9]), "=f"(d[O + 10]), "=f"(d[O + 11]), "=f"(d[O + 12]), "=f"(d[O + 13]), "=f"(d[O + 14]), "=f"(d[O + 15]), "=f"(d[O + 16]), "=f"(d[O + 17]), "=f"(d[O + 18]), "=f"(d[O + 19]), "=f"(d[O + 20]), "=f"(d[O + 21]), "=f"(d[O + 22]), "=f"(d[O + 23]), "=f"(d[O + 24]), "=f"(d[O + 25]), "=f"(d[O + 26]), "=f"(d[O + 27]), "=f"(d[O + 28]), "=f"(d[O + 29]), "=f"(d[O + 30]), "=f"(d[O + 31]), "=f"(d[O + 32]), "=f"(d[O + 33]), "=f"(d[O + 34]), "=f"(d[O + 35]), "=f"(d[O + 36]), "=f"(d[O + 37]), "=f"(d[O + 38]), "=f"(d[O + 39]), "=f"(d[O + 40]), "=f"(d[O + 41]), "=f"(d[O + 42]), "=f"(d[O + 43]), "=f"(d[O + 44]), "=f"(d[O + 45]), "=f"(d[O + 46]), "=f"(d[O + 47])
    : "r"(a0), "r"(a1), "r"(a2), "r"(a3), "l"(db));
  db += st;
}
template<int O, int SD, int L> __device__ __forceinline__ void rs48(float (&d)[L], uint32_t a0, uint32_t a1, uint32_t a2, uint32_t a3, uint64_t& db, uint32_t st) {
  if (SD) asm volatile("{\n.reg .pred p;\nsetp.ne.b32 p, 1, 0;\n"
    "wgmma.mma_async.sync.aligned.m64n48k16.f32.bf16.bf16 {%0, %1, %2, %3, %4, %5, %6, %7, %8, %9, %10, %11, %12, %13, %14, %15, %16, %17, %18, %19, %20, %21, %22, %23}, {%24, %25, %26, %27}, %28, p, 1, 1, 1;\n}\n"
    : "+f"(d[O + 0]), "+f"(d[O + 1]), "+f"(d[O + 2]), "+f"(d[O + 3]), "+f"(d[O + 4]), "+f"(d[O + 5]), "+f"(d[O + 6]), "+f"(d[O + 7]), "+f"(d[O + 8]), "+f"(d[O + 9]), "+f"(d[O + 10]), "+f"(d[O + 11]), "+f"(d[O + 12]), "+f"(d[O + 13]), "+f"(d[O + 14]), "+f"(d[O + 15]), "+f"(d[O + 16]), "+f"(d[O + 17]), "+f"(d[O + 18]), "+f"(d[O + 19]), "+f"(d[O + 20]), "+f"(d[O + 21]), "+f"(d[O + 22]), "+f"(d[O + 23])
    : "r"(a0), "r"(a1), "r"(a2), "r"(a3), "l"(db));
  else asm volatile("{\n.reg .pred p;\nsetp.ne.b32 p, 0, 0;\n"
    "wgmma.mma_async.sync.aligned.m64n48k16.f32.bf16.bf16 {%0, %1, %2, %3, %4, %5, %6, %7, %8, %9, %10, %11, %12, %13, %14, %15, %16, %17, %18, %19, %20, %21, %22, %23}, {%24, %25, %26, %27}, %28, p, 1, 1, 1;\n}\n"
    : "=f"(d[O + 0]), "=f"(d[O + 1]), "=f"(d[O + 2]), "=f"(d[O + 3]), "=f"(d[O + 4]), "=f"(d[O + 5]), "=f"(d[O + 6]), "=f"(d[O + 7]), "=f"(d[O + 8]), "=f"(d[O + 9]), "=f"(d[O + 10]), "=f"(d[O + 11]), "=f"(d[O + 12]), "=f"(d[O + 13]), "=f"(d[O + 14]), "=f"(d[O + 15]), "=f"(d[O + 16]), "=f"(d[O + 17]), "=f"(d[O + 18]), "=f"(d[O + 19]), "=f"(d[O + 20]), "=f"(d[O + 21]), "=f"(d[O + 22]), "=f"(d[O + 23])
    : "r"(a0), "r"(a1), "r"(a2), "r"(a3), "l"(db));
  db += st;
}
template<int O, int SD, int L> __device__ __forceinline__ void rs128(float (&d)[L], uint32_t a0, uint32_t a1, uint32_t a2, uint32_t a3, uint64_t& db, uint32_t st) {
  if (SD) asm volatile("{\n.reg .pred p;\nsetp.ne.b32 p, 1, 0;\n"
    "wgmma.mma_async.sync.aligned.m64n128k16.f32.bf16.bf16 {%0, %1, %2, %3, %4, %5, %6, %7, %8, %9, %10, %11, %12, %13, %14, %15, %16, %17, %18, %19, %20, %21, %22, %23, %24, %25, %26, %27, %28, %29, %30, %31, %32, %33, %34, %35, %36, %37, %38, %39, %40, %41, %42, %43, %44, %45, %46, %47, %48, %49, %50, %51, %52, %53, %54, %55, %56, %57, %58, %59, %60, %61, %62, %63}, {%64, %65, %66, %67}, %68, p, 1, 1, 1;\n}\n"
    : "+f"(d[O + 0]), "+f"(d[O + 1]), "+f"(d[O + 2]), "+f"(d[O + 3]), "+f"(d[O + 4]), "+f"(d[O + 5]), "+f"(d[O + 6]), "+f"(d[O + 7]), "+f"(d[O + 8]), "+f"(d[O + 9]), "+f"(d[O + 10]), "+f"(d[O + 11]), "+f"(d[O + 12]), "+f"(d[O + 13]), "+f"(d[O + 14]), "+f"(d[O + 15]), "+f"(d[O + 16]), "+f"(d[O + 17]), "+f"(d[O + 18]), "+f"(d[O + 19]), "+f"(d[O + 20]), "+f"(d[O + 21]), "+f"(d[O + 22]), "+f"(d[O + 23]), "+f"(d[O + 24]), "+f"(d[O + 25]), "+f"(d[O + 26]), "+f"(d[O + 27]), "+f"(d[O + 28]), "+f"(d[O + 29]), "+f"(d[O + 30]), "+f"(d[O + 31]), "+f"(d[O + 32]), "+f"(d[O + 33]), "+f"(d[O + 34]), "+f"(d[O + 35]), "+f"(d[O + 36]), "+f"(d[O + 37]), "+f"(d[O + 38]), "+f"(d[O + 39]), "+f"(d[O + 40]), "+f"(d[O + 41]), "+f"(d[O + 42]), "+f"(d[O + 43]), "+f"(d[O + 44]), "+f"(d[O + 45]), "+f"(d[O + 46]), "+f"(d[O + 47]), "+f"(d[O + 48]), "+f"(d[O + 49]), "+f"(d[O + 50]), "+f"(d[O + 51]), "+f"(d[O + 52]), "+f"(d[O + 53]), "+f"(d[O + 54]), "+f"(d[O + 55]), "+f"(d[O + 56]), "+f"(d[O + 57]), "+f"(d[O + 58]), "+f"(d[O + 59]), "+f"(d[O + 60]), "+f"(d[O + 61]), "+f"(d[O + 62]), "+f"(d[O + 63])
    : "r"(a0), "r"(a1), "r"(a2), "r"(a3), "l"(db));
  else asm volatile("{\n.reg .pred p;\nsetp.ne.b32 p, 0, 0;\n"
    "wgmma.mma_async.sync.aligned.m64n128k16.f32.bf16.bf16 {%0, %1, %2, %3, %4, %5, %6, %7, %8, %9, %10, %11, %12, %13, %14, %15, %16, %17, %18, %19, %20, %21, %22, %23, %24, %25, %26, %27, %28, %29, %30, %31, %32, %33, %34, %35, %36, %37, %38, %39, %40, %41, %42, %43, %44, %45, %46, %47, %48, %49, %50, %51, %52, %53, %54, %55, %56, %57, %58, %59, %60, %61, %62, %63}, {%64, %65, %66, %67}, %68, p, 1, 1, 1;\n}\n"
    : "=f"(d[O + 0]), "=f"(d[O + 1]), "=f"(d[O + 2]), "=f"(d[O + 3]), "=f"(d[O + 4]), "=f"(d[O + 5]), "=f"(d[O + 6]), "=f"(d[O + 7]), "=f"(d[O + 8]), "=f"(d[O + 9]), "=f"(d[O + 10]), "=f"(d[O + 11]), "=f"(d[O + 12]), "=f"(d[O + 13]), "=f"(d[O + 14]), "=f"(d[O + 15]), "=f"(d[O + 16]), "=f"(d[O + 17]), "=f"(d[O + 18]), "=f"(d[O + 19]), "=f"(d[O + 20]), "=f"(d[O + 21]), "=f"(d[O + 22]), "=f"(d[O + 23]), "=f"(d[O + 24]), "=f"(d[O + 25]), "=f"(d[O + 26]), "=f"(d[O + 27]), "=f"(d[O + 28]), "=f"(d[O + 29]), "=f"(d[O + 30]), "=f"(d[O + 31]), "=f"(d[O + 32]), "=f"(d[O + 33]), "=f"(d[O + 34]), "=f"(d[O + 35]), "=f"(d[O + 36]), "=f"(d[O + 37]), "=f"(d[O + 38]), "=f"(d[O + 39]), "=f"(d[O + 40]), "=f"(d[O + 41]), "=f"(d[O + 42]), "=f"(d[O + 43]), "=f"(d[O + 44]), "=f"(d[O + 45]), "=f"(d[O + 46]), "=f"(d[O + 47]), "=f"(d[O + 48]), "=f"(d[O + 49]), "=f"(d[O + 50]), "=f"(d[O + 51]), "=f"(d[O + 52]), "=f"(d[O + 53]), "=f"(d[O + 54]), "=f"(d[O + 55]), "=f"(d[O + 56]), "=f"(d[O + 57]), "=f"(d[O + 58]), "=f"(d[O + 59]), "=f"(d[O + 60]), "=f"(d[O + 61]), "=f"(d[O + 62]), "=f"(d[O + 63])
    : "r"(a0), "r"(a1), "r"(a2), "r"(a3), "l"(db));
  db += st;
}
template<int O, int SD, int L> __device__ __forceinline__ void rs32(float (&d)[L], uint32_t a0, uint32_t a1, uint32_t a2, uint32_t a3, uint64_t& db, uint32_t st) {
  if (SD) asm volatile("{\n.reg .pred p;\nsetp.ne.b32 p, 1, 0;\n"
    "wgmma.mma_async.sync.aligned.m64n32k16.f32.bf16.bf16 {%0, %1, %2, %3, %4, %5, %6, %7, %8, %9, %10, %11, %12, %13, %14, %15}, {%16, %17, %18, %19}, %20, p, 1, 1, 1;\n}\n"
    : "+f"(d[O + 0]), "+f"(d[O + 1]), "+f"(d[O + 2]), "+f"(d[O + 3]), "+f"(d[O + 4]), "+f"(d[O + 5]), "+f"(d[O + 6]), "+f"(d[O + 7]), "+f"(d[O + 8]), "+f"(d[O + 9]), "+f"(d[O + 10]), "+f"(d[O + 11]), "+f"(d[O + 12]), "+f"(d[O + 13]), "+f"(d[O + 14]), "+f"(d[O + 15])
    : "r"(a0), "r"(a1), "r"(a2), "r"(a3), "l"(db));
  else asm volatile("{\n.reg .pred p;\nsetp.ne.b32 p, 0, 0;\n"
    "wgmma.mma_async.sync.aligned.m64n32k16.f32.bf16.bf16 {%0, %1, %2, %3, %4, %5, %6, %7, %8, %9, %10, %11, %12, %13, %14, %15}, {%16, %17, %18, %19}, %20, p, 1, 1, 1;\n}\n"
    : "=f"(d[O + 0]), "=f"(d[O + 1]), "=f"(d[O + 2]), "=f"(d[O + 3]), "=f"(d[O + 4]), "=f"(d[O + 5]), "=f"(d[O + 6]), "=f"(d[O + 7]), "=f"(d[O + 8]), "=f"(d[O + 9]), "=f"(d[O + 10]), "=f"(d[O + 11]), "=f"(d[O + 12]), "=f"(d[O + 13]), "=f"(d[O + 14]), "=f"(d[O + 15])
    : "r"(a0), "r"(a1), "r"(a2), "r"(a3), "l"(db));
  db += st;
}
template<int O, int SD, int L> __device__ __forceinline__ void rs80(float (&d)[L], uint32_t a0, uint32_t a1, uint32_t a2, uint32_t a3, uint64_t& db, uint32_t st) {
  if (SD) asm volatile("{\n.reg .pred p;\nsetp.ne.b32 p, 1, 0;\n"
    "wgmma.mma_async.sync.aligned.m64n80k16.f32.bf16.bf16 {%0, %1, %2, %3, %4, %5, %6, %7, %8, %9, %10, %11, %12, %13, %14, %15, %16, %17, %18, %19, %20, %21, %22, %23, %24, %25, %26, %27, %28, %29, %30, %31, %32, %33, %34, %35, %36, %37, %38, %39}, {%40, %41, %42, %43}, %44, p, 1, 1, 1;\n}\n"
    : "+f"(d[O + 0]), "+f"(d[O + 1]), "+f"(d[O + 2]), "+f"(d[O + 3]), "+f"(d[O + 4]), "+f"(d[O + 5]), "+f"(d[O + 6]), "+f"(d[O + 7]), "+f"(d[O + 8]), "+f"(d[O + 9]), "+f"(d[O + 10]), "+f"(d[O + 11]), "+f"(d[O + 12]), "+f"(d[O + 13]), "+f"(d[O + 14]), "+f"(d[O + 15]), "+f"(d[O + 16]), "+f"(d[O + 17]), "+f"(d[O + 18]), "+f"(d[O + 19]), "+f"(d[O + 20]), "+f"(d[O + 21]), "+f"(d[O + 22]), "+f"(d[O + 23]), "+f"(d[O + 24]), "+f"(d[O + 25]), "+f"(d[O + 26]), "+f"(d[O + 27]), "+f"(d[O + 28]), "+f"(d[O + 29]), "+f"(d[O + 30]), "+f"(d[O + 31]), "+f"(d[O + 32]), "+f"(d[O + 33]), "+f"(d[O + 34]), "+f"(d[O + 35]), "+f"(d[O + 36]), "+f"(d[O + 37]), "+f"(d[O + 38]), "+f"(d[O + 39])
    : "r"(a0), "r"(a1), "r"(a2), "r"(a3), "l"(db));
  else asm volatile("{\n.reg .pred p;\nsetp.ne.b32 p, 0, 0;\n"
    "wgmma.mma_async.sync.aligned.m64n80k16.f32.bf16.bf16 {%0, %1, %2, %3, %4, %5, %6, %7, %8, %9, %10, %11, %12, %13, %14, %15, %16, %17, %18, %19, %20, %21, %22, %23, %24, %25, %26, %27, %28, %29, %30, %31, %32, %33, %34, %35, %36, %37, %38, %39}, {%40, %41, %42, %43}, %44, p, 1, 1, 1;\n}\n"
    : "=f"(d[O + 0]), "=f"(d[O + 1]), "=f"(d[O + 2]), "=f"(d[O + 3]), "=f"(d[O + 4]), "=f"(d[O + 5]), "=f"(d[O + 6]), "=f"(d[O + 7]), "=f"(d[O + 8]), "=f"(d[O + 9]), "=f"(d[O + 10]), "=f"(d[O + 11]), "=f"(d[O + 12]), "=f"(d[O + 13]), "=f"(d[O + 14]), "=f"(d[O + 15]), "=f"(d[O + 16]), "=f"(d[O + 17]), "=f"(d[O + 18]), "=f"(d[O + 19]), "=f"(d[O + 20]), "=f"(d[O + 21]), "=f"(d[O + 22]), "=f"(d[O + 23]), "=f"(d[O + 24]), "=f"(d[O + 25]), "=f"(d[O + 26]), "=f"(d[O + 27]), "=f"(d[O + 28]), "=f"(d[O + 29]), "=f"(d[O + 30]), "=f"(d[O + 31]), "=f"(d[O + 32]), "=f"(d[O + 33]), "=f"(d[O + 34]), "=f"(d[O + 35]), "=f"(d[O + 36]), "=f"(d[O + 37]), "=f"(d[O + 38]), "=f"(d[O + 39])
    : "r"(a0), "r"(a1), "r"(a2), "r"(a3), "l"(db));
  db += st;
}
template<int O, int SD, int L> __device__ __forceinline__ void rs88k(float (&d)[L], uint32_t a0, uint32_t a1, uint32_t a2, uint32_t a3, uint64_t& db, uint32_t st) {
  if (SD) asm volatile("{\n.reg .pred p;\nsetp.ne.b32 p, 1, 0;\n"
    "wgmma.mma_async.sync.aligned.m64n88k16.f32.bf16.bf16 {%0, %1, %2, %3, %4, %5, %6, %7, %8, %9, %10, %11, %12, %13, %14, %15, %16, %17, %18, %19, %20, %21, %22, %23, %24, %25, %26, %27, %28, %29, %30, %31, %32, %33, %34, %35, %36, %37, %38, %39, %40, %41, %42, %43}, {%44, %45, %46, %47}, %48, p, 1, 1, 0;\n}\n"
    : "+f"(d[O + 0]), "+f"(d[O + 1]), "+f"(d[O + 2]), "+f"(d[O + 3]), "+f"(d[O + 4]), "+f"(d[O + 5]), "+f"(d[O + 6]), "+f"(d[O + 7]), "+f"(d[O + 8]), "+f"(d[O + 9]), "+f"(d[O + 10]), "+f"(d[O + 11]), "+f"(d[O + 12]), "+f"(d[O + 13]), "+f"(d[O + 14]), "+f"(d[O + 15]), "+f"(d[O + 16]), "+f"(d[O + 17]), "+f"(d[O + 18]), "+f"(d[O + 19]), "+f"(d[O + 20]), "+f"(d[O + 21]), "+f"(d[O + 22]), "+f"(d[O + 23]), "+f"(d[O + 24]), "+f"(d[O + 25]), "+f"(d[O + 26]), "+f"(d[O + 27]), "+f"(d[O + 28]), "+f"(d[O + 29]), "+f"(d[O + 30]), "+f"(d[O + 31]), "+f"(d[O + 32]), "+f"(d[O + 33]), "+f"(d[O + 34]), "+f"(d[O + 35]), "+f"(d[O + 36]), "+f"(d[O + 37]), "+f"(d[O + 38]), "+f"(d[O + 39]), "+f"(d[O + 40]), "+f"(d[O + 41]), "+f"(d[O + 42]), "+f"(d[O + 43])
    : "r"(a0), "r"(a1), "r"(a2), "r"(a3), "l"(db));
  else asm volatile("{\n.reg .pred p;\nsetp.ne.b32 p, 0, 0;\n"
    "wgmma.mma_async.sync.aligned.m64n88k16.f32.bf16.bf16 {%0, %1, %2, %3, %4, %5, %6, %7, %8, %9, %10, %11, %12, %13, %14, %15, %16, %17, %18, %19, %20, %21, %22, %23, %24, %25, %26, %27, %28, %29, %30, %31, %32, %33, %34, %35, %36, %37, %38, %39, %40, %41, %42, %43}, {%44, %45, %46, %47}, %48, p, 1, 1, 0;\n}\n"
    : "=f"(d[O + 0]), "=f"(d[O + 1]), "=f"(d[O + 2]), "=f"(d[O + 3]), "=f"(d[O + 4]), "=f"(d[O + 5]), "=f"(d[O + 6]), "=f"(d[O + 7]), "=f"(d[O + 8]), "=f"(d[O + 9]), "=f"(d[O + 10]), "=f"(d[O + 11]), "=f"(d[O + 12]), "=f"(d[O + 13]), "=f"(d[O + 14]), "=f"(d[O + 15]), "=f"(d[O + 16]), "=f"(d[O + 17]), "=f"(d[O + 18]), "=f"(d[O + 19]), "=f"(d[O + 20]), "=f"(d[O + 21]), "=f"(d[O + 22]), "=f"(d[O + 23]), "=f"(d[O + 24]), "=f"(d[O + 25]), "=f"(d[O + 26]), "=f"(d[O + 27]), "=f"(d[O + 28]), "=f"(d[O + 29]), "=f"(d[O + 30]), "=f"(d[O + 31]), "=f"(d[O + 32]), "=f"(d[O + 33]), "=f"(d[O + 34]), "=f"(d[O + 35]), "=f"(d[O + 36]), "=f"(d[O + 37]), "=f"(d[O + 38]), "=f"(d[O + 39]), "=f"(d[O + 40]), "=f"(d[O + 41]), "=f"(d[O + 42]), "=f"(d[O + 43])
    : "r"(a0), "r"(a1), "r"(a2), "r"(a3), "l"(db));
  db += st;
}
template<int O, uint32_t HI, int SD, int L> __device__ __forceinline__ void ss48tt(float (&d)[L], uint32_t alo, uint32_t blo) {
  if (SD) asm volatile("{\n.reg .pred p;\n.reg .b64 da, db;\nsetp.ne.b32 p, 1, 0;\nmov.b64 da, {%24, %26};\nmov.b64 db, {%25, %26};\n"
    "wgmma.mma_async.sync.aligned.m64n48k16.f32.bf16.bf16 {%0, %1, %2, %3, %4, %5, %6, %7, %8, %9, %10, %11, %12, %13, %14, %15, %16, %17, %18, %19, %20, %21, %22, %23}, da, db, p, 1, 1, 1, 1;\n}\n"
    : "+f"(d[O + 0]), "+f"(d[O + 1]), "+f"(d[O + 2]), "+f"(d[O + 3]), "+f"(d[O + 4]), "+f"(d[O + 5]), "+f"(d[O + 6]), "+f"(d[O + 7]), "+f"(d[O + 8]), "+f"(d[O + 9]), "+f"(d[O + 10]), "+f"(d[O + 11]), "+f"(d[O + 12]), "+f"(d[O + 13]), "+f"(d[O + 14]), "+f"(d[O + 15]), "+f"(d[O + 16]), "+f"(d[O + 17]), "+f"(d[O + 18]), "+f"(d[O + 19]), "+f"(d[O + 20]), "+f"(d[O + 21]), "+f"(d[O + 22]), "+f"(d[O + 23])
    : "r"(alo), "r"(blo), "n"(HI));
  else asm volatile("{\n.reg .pred p;\n.reg .b64 da, db;\nsetp.ne.b32 p, 0, 0;\nmov.b64 da, {%24, %26};\nmov.b64 db, {%25, %26};\n"
    "wgmma.mma_async.sync.aligned.m64n48k16.f32.bf16.bf16 {%0, %1, %2, %3, %4, %5, %6, %7, %8, %9, %10, %11, %12, %13, %14, %15, %16, %17, %18, %19, %20, %21, %22, %23}, da, db, p, 1, 1, 1, 1;\n}\n"
    : "=f"(d[O + 0]), "=f"(d[O + 1]), "=f"(d[O + 2]), "=f"(d[O + 3]), "=f"(d[O + 4]), "=f"(d[O + 5]), "=f"(d[O + 6]), "=f"(d[O + 7]), "=f"(d[O + 8]), "=f"(d[O + 9]), "=f"(d[O + 10]), "=f"(d[O + 11]), "=f"(d[O + 12]), "=f"(d[O + 13]), "=f"(d[O + 14]), "=f"(d[O + 15]), "=f"(d[O + 16]), "=f"(d[O + 17]), "=f"(d[O + 18]), "=f"(d[O + 19]), "=f"(d[O + 20]), "=f"(d[O + 21]), "=f"(d[O + 22]), "=f"(d[O + 23])
    : "r"(alo), "r"(blo), "n"(HI));
}

constexpr uint32_t HI128 = 0x40000040u;
constexpr uint32_t HI64 = 0x80000020u;
constexpr uint32_t HI32 = 0xC0000010u;

__device__ __forceinline__ uint64_t desc(uint32_t lo, uint32_t hi) { return (uint64_t)hi << 32 | lo; }
__device__ __forceinline__ bool elect() {
  uint32_t p;
  asm volatile("{\n.reg .pred p;\nelect.sync _|p, 0xffffffff;\nselp.u32 %0, 1, 0, p;\n}" : "=r"(p));
  return p;
}
struct Ring {
  uint32_t fb, lo, ph;
  __device__ __forceinline__ void at(uint32_t it, uint32_t base) {
    const uint32_t rev = (it * 205u) >> 11, slot = it - rev * NSLOT;
    fb = base + OFF_BAR + 8 * slot; lo = (base >> 4) + slot * (SLOT / 16); ph = rev & 1;
  }
  template<int N> __device__ __forceinline__ void next(uint32_t bars) {
    fb += 8 * N; lo += N * (SLOT / 16);
    if (fb >= bars + 8 * NSLOT) { fb -= 8 * NSLOT; lo -= NSLOT * (SLOT / 16); ph ^= 1; }
  }
};

template<int N>
__device__ __forceinline__ void tile_mma(float (&acc)[48], const uint32_t (&a)[160], int t, uint32_t base, bool lane0, uint32_t sig) {
  const uint32_t bars = base + OFF_BAR;
  uint32_t prev = 0;
  Ring r;
  r.at(8 * t + (t >= 2 ? 2 : 0), base);
  TWAIT(r.fb, r.ph, 96 + (sig - 3) * 16 + t);
  #pragma unroll
  for (int st = 0; st < 8; st++) {
    uint64_t db = desc(r.lo | (640u << 16), HI128), d2 = desc(r.lo + 640, HI128);
    const uint32_t cur = r.fb;
    wg_fence();
    #pragma unroll
    for (int kk = 0; kk < 5; kk++) {
      const int k = 4 * (st * 5 + kk);
      if (k == 0) {
        if (N == 80) rs80<0, 0>(acc, a[k], a[k + 1], a[k + 2], a[k + 3], db, 128);
        else if (N == 96) rs96<0, 0>(acc, a[k], a[k + 1], a[k + 2], a[k + 3], db, 128);
        else { rs48<0, 0>(acc, a[k], a[k + 1], a[k + 2], a[k + 3], db, 128); rs48<24, 0>(acc, a[k], a[k + 1], a[k + 2], a[k + 3], d2, 128); }
      } else {
        if (N == 80) rs80<0, 1>(acc, a[k], a[k + 1], a[k + 2], a[k + 3], db, 128);
        else if (N == 96) rs96<0, 1>(acc, a[k], a[k + 1], a[k + 2], a[k + 3], db, 128);
        else { rs48<0, 1>(acc, a[k], a[k + 1], a[k + 2], a[k + 3], db, 128); rs48<24, 1>(acc, a[k], a[k + 1], a[k + 2], a[k + 3], d2, 128); }
      }
    }
    wg_commit();
    if (st == (N == 80 ? S1 : S0) - 1) asm volatile("bar.arrive %0, 256;" :: "r"(sig) : "memory");
    r.next<1>(bars);
    if (st > 0) { wg_wait<1>(); if (lane0) mbar_arrive(prev + 80); }
    if (st < 7) TWAIT(r.fb, r.ph, 96 + (sig - 3) * 16 + t);
    prev = cur;
  }
  wg_wait<0>();
  if (lane0) mbar_arrive(prev + 80);
  pin<0, N == 80 ? 40 : 48>(acc);
}

struct Maps { CUtensorMap x, qkv64, qkv16, w1a, w1b, w3a, w3b, w1c, w3c, w2a, w2b, woa, wob, xa, xb, oa, ob; };

__global__ void __launch_bounds__(384, 1)
fused_kernel(const __grid_constant__ Maps M) {
  extern __shared__ __align__(1024) uint8_t smem_raw[];
  asm volatile("prefetch.tensormap [%0];" :: "l"(&M.x) : "memory");
  const uint32_t base = (smem_u32(smem_raw) + 1023) & ~1023u;
  const uint32_t bars = base + OFF_BAR;
  const int tid = threadIdx.x;
  const int warp = __shfl_sync(0xffffffffu, tid >> 5, 0);
  const int b = blockIdx.x;
  const int rb = ((b >> 4) & 3) * 4 + (b & 1) + ((b >> 2) & 2), role = b >> 6, p = (b >> 1) & 3, mate = b ^ 64;
  if ((warp >> 1) == 4 && elect()) {
    const int w = warp & 1;
    if (!w) PROFT_(0);
    uint32_t xb = bars + 8 * (B_XFULL + 5 * w), xd = base + (3 + 4 * w) * SLOT;
    #pragma unroll
    for (int i = 0; i < 5; i++) mbar_init(xb + 8 * i, 1);
    asm volatile("fence.proxy.async.shared::cta;" ::: "memory");
    #pragma unroll 1
    for (int i = -DLY * w; i < 10; i += 2) {
      if (i < 0) continue;
      mbar_expect(xb, 16384);
      tma3d(xd, &M.x, 0, rb * 128 + 64 * w, i, xb);
      xb += 8; xd += 16384 + (i ? 0 : 4096 * w);
    }
  }
  const int g = 2 * p + role;
  const int nt = role ? 7 : 8;
  const int cl = 160 * p + (p & 1) * 32 + 64 * role, ch = 160 * p + (~p & 1) * 128;

  if (warp < 8) goto CONSUMER;
  asm volatile("setmaxnreg.dec.sync.aligned.u32 24;");
  if (elect()) {
    if (warp == 9) {
      #pragma unroll
      for (int i = 0; i < 20; i++) mbar_init(bars + 8 * i, i < 10 ? 1 : 8);
      asm volatile("fence.proxy.async.shared::cta;" ::: "memory");
    } else if (warp == 10) {
      #pragma unroll
      for (int i = 30; i < 51; i++) mbar_init(bars + 8 * i, i < 43 ? 4 : i == B_KVRDY ? 2 : 1);
      mbar_init(bars + 8 * (B_AUXF + 10), 8);
      asm volatile("fence.proxy.async.shared::cta;" ::: "memory");
    } else if (warp == 11) {
      #pragma unroll 1
      for (int i = 1; i < 17; i++) asm volatile("prefetch.tensormap [%0];" :: "l"(&M.x + i) : "memory");
    }
  }
  asm volatile("bar.sync 0, 384;" ::: "memory");
  if (warp >= 10) goto PUBLISHER;
  {
      if (elect()) {
        const int w = warp - 8;
        Ring r{bars + 8 * w, (base + w * SLOT) >> 4, 1};
        uint32_t fb, dst;
        auto acquire = [&](uint32_t bytes) {
          mbar_wait(r.fb + 80, r.ph);
          fb = r.fb; dst = r.lo << 4;
          mbar_expect(fb, bytes);
          r.next<2>(bars);
        };
        #pragma unroll 1
        for (int t = 0; t < nt; t++) {
          const CUtensorMap* m0 = &M.qkv64; const CUtensorMap* m1 = &M.qkv16;
          int c0, c1; uint32_t bytes = 15360;
          if (t < 2 || t == nt - 1) { c0 = (t < 2 ? 640 + 640 * t : 0) + 80 * g; c1 = c0 + 64; bytes = 12800; }
          else if (t == 6) { c0 = c1 = 1536 + 48 * p; m0 = &M.w1c; m1 = &M.w3c; }
          else {
            c0 = c1 = 96 * (4 * (t - 2 & ~1) + g);
            if (t & 1) { m0 = &M.w3a; m1 = &M.w1b; c0 += 32; c1 += 64; } else { m0 = &M.w1a; m1 = &M.w3b; }
          }
          #pragma unroll 1
          for (int st = w; st < 8; st += 2) {
            const int it = 8 * t + st;
            if (it >= 3 && it < 10) mbar_wait(bars + 8 * (B_XFREE + (it < 7 ? 0 : it == 7 ? 2 : 1)), 0);
            acquire(bytes);
            tma2d(dst, m0, c0, 80 * st, fb);
            tma2d(dst + 10240, m1, c1, 80 * st, fb);
          }
          if (t == 1) acquire(0);
        }
        PROFT(40 + 8 * w);
        const int k0 = role ? 0 : NY, k1 = role ? NY : 108;
        if (w == 0) {
          #pragma unroll 1
          for (int k = k0; k < k1; k += k == k0 ? 2 : 4) {
            if (k == k0 + 18) {
              mbar_wait(bars + 8 * (B_EV + nt - 4), 0);
              mbar_wait(bars + 8 * (B_EV + nt + 1), 0);
              fb = bars + 8 * B_AUXF; dst = base + OFF_AUX;
              mbar_expect(fb, 20480);
            } else acquire(20480);
            tma2d(dst, &M.w2a, cl, 16 * k, fb);
            tma2d(dst + 8192, &M.w2a, cl + 64 - 128 * role, 16 * k, fb);
            tma2d(dst + 16384, &M.w2b, ch, 16 * k, fb);
            PROFT(188 + (k - k0 + 2) / 4);
          }
          #pragma unroll 1
          for (int m = 0; m < 8; m++) {
            const int gm = m < 4 ? 2 * m + 1 : 2 * m - 8;
            acquire(12800);
            tma2d(dst, &M.woa, cl, 80 * gm, fb);
            tma2d(dst + 10240, &M.wob, ch + 16 * role, 80 * gm, fb);
            if (m == 0) {
              mbar_expect(bars + 8 * B_XRES, 20480);
              tma2d(base + OFF_AUX, &M.xa, cl, rb * 128, bars + 8 * B_XRES);
              tma2d(base + OFF_AUX + 16384, &M.xb, ch + 16 * role, rb * 128, bars + 8 * B_XRES);
            }
            PROFT(208 + m);
          }
        } else {
          auto ready = [&](int i) { mbar_wait(bars + 8 * (B_OK + i), 0); asm volatile("fence.proxy.async.global;" ::: "memory"); };
          #pragma unroll 1
          for (int k = k0, n = 2; k < k1; k += n, n = 4) {
            if (k == k0 || k == (role ? 46 : 96)) ready(k != k0);
            acquire(n * 4096);
            bulk(dst, g_h + (rb * 108 + k) * 256, n * 4096, fb);
            PROFT(168 + (k - k0 + 2) / 4);
          }
          PROFT(49);
          #pragma unroll 1
          for (int m = 0; m < 8; m++) {
            if (!(m & 3)) ready(2 + (m >> 2));
            acquire(20480);
            bulk(dst, g_o + (rb * 40 + 5 * (m < 4 ? 2 * m + 1 : 2 * m - 8)) * 256, 20480, fb);
            PROFT(216 + m);
          }
        }
      }
    PROFEND();
    return;
  }
CONSUMER:
  {
    asm volatile("setmaxnreg.inc.sync.aligned.u32 240;");
    const int wg = warp >> 2, w4 = warp & 3, lane = tid & 31;
    const bool lane0 = lane == 0;
    uint32_t a[160];
    float r0, r1;
    asm volatile("bar.sync 0, 384;" ::: "memory");
    {
      const int row = w4 * 16 + (lane & 15);
      const uint32_t xa = base + (wg ? 7 : 3) * SLOT + row * 128, xb = xa + wg * 4096;
      float st[2][4];
      #pragma unroll
      for (int i = 0; i < 8; i++) st[i >> 2][i & 3] = 0.f;
      #pragma unroll
      for (int i = 0; i < 10; i++) {
        if (i == 0) PROFC(32 + wg * 4);
        if (!(i & 1)) mbar_wait(bars + 8 * (B_XFULL + wg * 5 + (i >> 1)), 0);
        if (i == 0) PROFC(33 + wg * 4);
        if (i == 8) PROFC(34 + wg * 4);
        #pragma unroll
        for (int j = 0; j < 4; j++) {
          const int k = 16 * i + 4 * j;
          asm volatile("ldmatrix.sync.aligned.m8n8.x4.shared.b16 {%0,%1,%2,%3}, [%4];" : "=r"(a[k]), "=r"(a[k + 1]), "=r"(a[k + 2]), "=r"(a[k + 3])
                       : "r"((i < 2 ? xa : xb) + i * 8192 + (((2 * j + (lane >> 4)) ^ (row & 7)) << 4)) : "memory");
        }
        if (i == 1 && lane0 && wg) mbar_arrive(bars + 8 * (B_XFREE + 2) + (a[31] & blockIdx.y));
        #pragma unroll
        for (int j = 0; j < 4; j++) { const int k = 16 * i + 4 * j; rowsum(st[j & 1], a[k], a[k + 1], a[k + 2], a[k + 3]); }
      }
      const float m0 = (st[0][0] + st[1][0]) * (1.f / 640), m1 = (st[0][2] + st[1][2]) * (1.f / 640);
      if (lane0) mbar_arrive(bars + 8 * (B_XFREE + wg) + (__float_as_uint(m0) & blockIdx.y));
      PROFC(35 + wg * 4);
      uint32_t b0 = pack(m0, m0), b1 = pack(m1, m1);
      uint32_t dep = 0;
      asm volatile("{\n.reg .pred p;\nsetp.ne.u32 p, %1, 0;\n@p bar.sync 6, 256;\n@p ld.shared.u32 %0, [%2];\n}" : "+r"(dep) : "r"(wg), "r"(base + OFF_EP) : "memory");
      b0 ^= dep & blockIdx.y; b1 ^= dep & blockIdx.y;
      float q0 = 0.f, q1 = 0.f;
      #pragma unroll
      for (int k = 0; k < XLN; k += 20) {
        #pragma unroll
        for (int j = 0; j < 20; j++) asm("sub.rn.bf16x2 %0, %0, %1;" : "+r"(a[k + j]) : "r"((j & 1) ? b1 : b0));
        uint32_t u0 = hmul(a[k], a[k]), u1 = hmul(a[k + 1], a[k + 1]);
        #pragma unroll
        for (int j = 2; j < 20; j += 2) { u0 = hfma(a[k + j], a[k + j], u0); u1 = hfma(a[k + j + 1], a[k + j + 1], u1); }
        q0 += blo(u0) + bhi(u0); q1 += blo(u1) + bhi(u1);
      }
      q0 += __shfl_xor_sync(0xffffffffu, q0, 1); q1 += __shfl_xor_sync(0xffffffffu, q1, 1);
      q0 += __shfl_xor_sync(0xffffffffu, q0, 2); q1 += __shfl_xor_sync(0xffffffffu, q1, 2);
      const float e0 = m0 - blo(b0), e1 = m1 - blo(b1);
      r0 = rsqrtf(fmaxf(fmaf(-e0, e0, q0 * (1.f / 640)), 0.f) + 1e-5f);
      r1 = rsqrtf(fmaxf(fmaf(-e1, e1, q1 * (1.f / 640)), 0.f) + 1e-5f);
    }
    asm volatile("{\n.reg .pred p;\nsetp.eq.u32 p, %0, 0;\n@p bar.arrive 6, 256;\n}" :: "r"(wg + (__float_as_uint(r0) & blockIdx.y)) : "memory");
    PROFL(1 + wg * 16);
    float acc[48];
    const uint32_t evb = bars + 8 * (B_EV + wg * 5);
    #pragma unroll 1
    for (int tv = 0;; tv++) {
      const int t = __shfl_sync(0xffffffffu, tv, 0);
      PROFL(64 + wg * 16 + t);
      if (wg || t) asm volatile("bar.sync %0, 256;" :: "r"(4 - wg) : "memory");
      if (t < 2 || t == nt - 1) {
        tile_mma<80>(acc, a, t, base, lane0, 3 + wg);
        if (t >= 2) break;
        PROFL(2 + t + wg * 16);
        asm volatile("" : "+f"(r0), "+f"(r1));
        const int lane = fresh_tid() & 31, t4 = lane & 3;
        const int row = w4 * 16 + (lane & 15);
        const uint32_t so = row * 32 + ((((lane >> 4) ^ (row >> 2)) & 1) << 4);
        const uint32_t PK = base + OFF_AUX + wg * 10240;
        if (t == 0) {
          const float k0 = r0 * LOG2E, k1 = r1 * LOG2E;
          mbar_wait(bars + 8 * (B_XFREE + 1), 0);
          #pragma unroll
          for (int i = 0; i < 5; i++)
            stsm4(PK + so + i * 2048, phi2<1>(acc[8 * i], acc[8 * i + 1], r0, k0), phi2<1>(acc[8 * i + 2], acc[8 * i + 3], r1, k1),
                  phi2<1>(acc[8 * i + 4], acc[8 * i + 5], r0, k0), phi2<1>(acc[8 * i + 6], acc[8 * i + 7], r1, k1));
          continue;
        }
        mbar_wait(bars + 8 * 6, 1);
        mbar_wait(bars + 8 * 7, 1);
        if (lane0) mbar_arrive(bars + 8 * (B_EMPTY + 7 - wg));
        const uint32_t VS = base + (6 + wg) * SLOT;
        {
          uint32_t v[20];
          #pragma unroll
          for (int i = 0; i < 20; i++) v[i] = pack(acc[2 * i], acc[2 * i + 1]);
          const float s0 = rcp(r0), s1 = rcp(r1);
          const uint32_t o0 = t4 == 0 ? pack(s0, s0 - blo(pack(s0, 0.f))) : 0u, o1 = t4 == 0 ? pack(s1, s1 - blo(pack(s1, 0.f))) : 0u;
          stsm4(VS + so, v[0], v[1], v[2], v[3]); stsm4(VS + so + 2048, v[4], v[5], v[6], v[7]); stsm4(VS + so + 4096, v[8], v[9], o0, o1);
          stsm4(VS + so + 6144, v[10], v[11], v[12], v[13]); stsm4(VS + so + 8192, v[14], v[15], v[16], v[17]); stsm4(VS + so + 10240, v[18], v[19], o0, o1);
        }
        asm volatile("fence.proxy.async.shared::cta;" ::: "memory");
        asm volatile("bar.sync %0, 128;" :: "r"(1 + wg) : "memory");
        const uint32_t al = (PK >> 4) | (128u << 16), bl = (VS >> 4) | (128u << 16);
        wg_fence();
        ss48tt<0, HI32, 0>(acc, al, bl); ss48tt<24, HI32, 0>(acc, al + 256, bl + 384);
        #pragma unroll
        for (int kk = 1; kk < 4; kk++) { ss48tt<0, HI32, 1>(acc, al + 32 * kk, bl + 32 * kk); ss48tt<24, HI32, 1>(acc, al + 256 + 32 * kk, bl + 384 + 32 * kk); }
        wg_commit();
        const int m0 = w4 * 16 + (lane >> 2);
        const uint32_t dst = VS + 12288 + m0 * 96 + t4 * 8;
        wg_wait<0>();
        pin<0, 48>(acc);
        #pragma unroll
        for (int i = 0; i < 4; i++) {
          const int j = i >> 1, hf = i & 1;
          const uint32_t d = m0 + 8 * hf - 8 * j;
          const int off = d >= 20 ? 20 : 0;
          const uint32_t dr = dst + (j * 40 + 8 * hf - 8 * j) * 96;
          const uint32_t e0 = d < 40 ? (uint32_t)(2 * t4 - off) : 1000u;
          #pragma unroll
          for (int jb = 0; jb < 5; jb++)
            asm volatile("{\n.reg .pred p;\nsetp.lt.u32 p, %0, 20;\n@p st.shared.v2.f32 [%1], {%2, %3};\n}"
                         :: "r"(e0 + 8 * jb), "r"(dr - off * 4 + 32 * jb), "f"(acc[24 * j + 4 * jb + 2 * hf]), "f"(acc[24 * j + 4 * jb + 2 * hf + 1]) : "memory");
          asm volatile("{\n.reg .pred p;\nsetp.lt.u32 p, %0, 2;\n@p st.shared.v2.f32 [%1], {%2, %3};\n}"
                       :: "r"((d < 40 ? 0 : 4) + t4), "r"(dr + 80), "f"(acc[24 * j + 20 + 2 * hf]), "f"(acc[24 * j + 21 + 2 * hf]) : "memory");
        }
        asm volatile("fence.proxy.async.shared::cta;" ::: "memory");
        __syncwarp();
        if (lane0) mbar_arrive(evb);
        PROFC(15 + wg * 16);
        continue;
      }
      if (t == 6) {
        tile_mma<48>(acc, a, t, base, lane0, 3 + wg);
        PROFL(2 + t + wg * 16);
        asm volatile("" : "+f"(r0), "+f"(r1));
        const float k0 = 0.5f * r0, k1 = 0.5f * r1;
        uint4* dst = g_h + (rb * 108 + 96 + 3 * p) * 256 + fresh_tid();
        #pragma unroll
        for (int s = 0; s < 3; s++) {
          uint32_t h[4];
          #pragma unroll
          for (int c = 0; c < 4; c++) {
            const int o = 8 * s + 2 * c; const float rr = (c & 1) ? r1 : r0, kk = (c & 1) ? k1 : k0;
            h[c] = pack(silu2(acc[o] * kk) * (acc[24 + o] * rr), silu2(acc[o + 1] * kk) * (acc[25 + o] * rr));
          }
          dst[s * 256] = make_uint4(h[0], h[1], h[2], h[3]);
        }
        __syncwarp();
        if (lane0) mbar_arrive(evb + 8 * 3);
        continue;
      }
      tile_mma<96>(acc, a, t, base, lane0, 3 + wg);
      PROFL(2 + t + wg * 16);
      asm volatile("" : "+f"(r0), "+f"(r1));
      const int tid = fresh_tid();
      const float k0 = 0.5f * r0, k1 = 0.5f * r1;
      const uint32_t stash = base + OFF_AUX + 20480 - wg * 4096 + (tid & 127) * 16;
      uint4* dst = g_h + (rb * 108 + 6 * (4 * (t - 2 & ~1) + g)) * 256 + tid;
      if (!(t & 1)) {
        #pragma unroll
        for (int s = 0; s < 4; s++) {
          uint32_t h[4];
          #pragma unroll
          for (int c = 0; c < 4; c++) {
            const int o = 8 * s + 2 * c; const float rr = (c & 1) ? r1 : r0, kk = (c & 1) ? k1 : k0;
            h[c] = s < 2 ? pack(silu2(acc[o] * kk) * (acc[32 + o] * rr), silu2(acc[o + 1] * kk) * (acc[33 + o] * rr)) : pack(silu2(acc[o] * kk), silu2(acc[o + 1] * kk));
          }
          if (s < 2) dst[s * 256] = make_uint4(h[0], h[1], h[2], h[3]); else sts128(stash + (s - 2) * 2048, h[0], h[1], h[2], h[3]);
        }
        continue;
      }
      #pragma unroll
      for (int s = 0; s < 4; s++) {
        uint32_t h[4];
        if (s < 2) {
          const uint4 u = lds128(stash + s * 2048);
          h[0] = pack(blo(u.x) * (acc[8 * s] * r0), bhi(u.x) * (acc[8 * s + 1] * r0)); h[1] = pack(blo(u.y) * (acc[8 * s + 2] * r1), bhi(u.y) * (acc[8 * s + 3] * r1));
          h[2] = pack(blo(u.z) * (acc[8 * s + 4] * r0), bhi(u.z) * (acc[8 * s + 5] * r0)); h[3] = pack(blo(u.w) * (acc[8 * s + 6] * r1), bhi(u.w) * (acc[8 * s + 7] * r1));
        } else {
          #pragma unroll
          for (int c = 0; c < 4; c++) {
            const int o = 8 * s + 2 * c; const float rr = (c & 1) ? r1 : r0, kk = (c & 1) ? k1 : k0;
            h[c] = pack(silu2(acc[16 + o] * kk) * (acc[o] * rr), silu2(acc[17 + o] * kk) * (acc[o + 1] * rr));
          }
        }
        dst[(2 + s) * 256] = make_uint4(h[0], h[1], h[2], h[3]);
      }
      __syncwarp();
      if (lane0) mbar_arrive(evb + 8 * (t >> 1));
    }
    float c1[64], c2[16];
    uint4 fa[3][5];
    Ring r;
    r.at(8 * nt + 2, base);
    {
      PROFL(9 + wg * 16);
      const int t4 = lane & 3;
      const float k0 = r0 * LOG2E, k1 = r1 * LOG2E;
      uint32_t q[20];
      #pragma unroll
      for (int i = 0; i < 20; i++) q[i] = phi2<0>(acc[2 * i], acc[2 * i + 1], (i & 1) ? r1 : r0, (i & 1) ? k1 : k0);
      mbar_wait(bars + 8 * B_KVRDY, 0);
      uint64_t db = desc(((base + OFF_AUX) >> 4) | (1u << 16), HI32);
      wg_fence();
      rs88k<0, 0>(acc, q[0], q[1], q[2], q[3], db, 176);
      #pragma unroll
      for (int s = 1; s < 5; s++) rs88k<0, 1>(acc, q[4 * s], q[4 * s + 1], q[4 * s + 2], q[4 * s + 3], db, 176);
      wg_commit();
      mbar_wait(r.fb + 8, r.ph);
      #pragma unroll
      for (int kk = 0; kk < 2; kk++) fa[0][kk] = lds128((r.lo << 4) + SLOT + kk * 4096 + tid * 16);
      #pragma unroll
      for (int i = 0; i < 64; i++) c1[i] = 0.f;
      #pragma unroll
      for (int i = 0; i < 16; i++) c2[i] = 0.f;
      pin<0, 64>(c1); pin<0, 16>(c2);
      mbar_wait(r.fb, r.ph);
      if (!wg) asm volatile("bar.sync 4, 256;" ::: "memory");
      wg_wait<0>();
      pin<0, 44>(acc);
      float dn[2][4];
      #pragma unroll
      for (int hf = 0; hf < 2; hf++) {
        const float u = rcp(acc[40 + 2 * hf] + 1e-6f), v = rcp(acc[41 + 2 * hf] + 1e-6f);
        dn[hf][0] = __shfl_sync(0xffffffffu, u, lane & 28); dn[hf][1] = __shfl_sync(0xffffffffu, v, lane & 28);
        dn[hf][2] = __shfl_sync(0xffffffffu, u, (lane & 28) + 1); dn[hf][3] = __shfl_sync(0xffffffffu, v, (lane & 28) + 1);
      }
      uint4* dst = g_o + (rb * 40 + 5 * g) * 256 + tid;
      #pragma unroll
      for (int s = 0; s < 5; s++) {
        uint32_t o[4];
        #pragma unroll
        for (int c = 0; c < 4; c++) {
          const int blk = 2 * s + (c >> 1), hf = c & 1;
          const float sc = blk == 2 ? (t4 < 2 ? dn[hf][0] : dn[hf][1]) : blk == 7 ? (t4 < 2 ? dn[hf][2] : dn[hf][3]) : dn[hf][(8 * blk) / 20];
          o[c] = pack(acc[4 * blk + 2 * hf] * sc, acc[4 * blk + 2 * hf + 1] * sc);
        }
        dst[s * 256] = make_uint4(o[0], o[1], o[2], o[3]);
      }
      __syncwarp();
      if (lane0) mbar_arrive(evb + 8 * (nt - 4));
      PROFL(10 + wg * 16);
    }
    {
      float c[40];
      uint4 xv[5], pv[5];
      uint32_t kp[20];
      uint32_t prev = 0;
      int sidx = 0;
      const int row = warp * 16 + (lane & 15);
      const uint32_t xa = base + OFF_AUX + row * 128, xs = ((lane >> 4) ^ row) & 7;
      const uint32_t xb = base + OFF_AUX + 16384 + row * 32 + ((((lane >> 4) ^ (row >> 2)) & 1) << 4);
      Ring wb = r;
      auto stage = [&](uint4 (&f)[5], int nk, uint4 (&fn)[5], int nn, bool fetch, bool rela, bool relb, int sel, auto pre, auto issue, auto extra) {
        Ring n = r; n.next<2>(bars);
        if (lane0 && rela) mbar_arrive(r.fb + 88 + (f[nk - 1].w & blockIdx.y));
        if (fetch) TWAIT(n.fb + 8, n.ph, 104 + wg * 16 + (sidx ? 2 : 0));
        #pragma unroll
        for (int kk = 0; kk < 5; kk++) if (kk < nn && fetch) fn[kk] = lds128((n.lo << 4) + SLOT + kk * 4096 + tid * 16);
        pre();
        wg_fence();
        issue(wb.lo);
        wg_commit();
        const uint32_t cur = wb.fb;
        wb = sel == 0 ? n : sel == 2 ? r : Ring{bars + 8 * B_AUXF, (base + OFF_AUX) >> 4, 0};
        if (fetch) TWAIT(wb.fb, wb.ph, 105 + wg * 16 + (sidx ? 2 : 0));
        extra();
        wg_wait<1>();
        if (lane0 && relb) mbar_arrive(prev + 80);
        prev = cur;
        r = n;
      };
      auto down = [&](uint4 (&f)[5], int nk, uint4 (&fn)[5], int nn, bool relb, int sel) {
        stage(f, nk, fn, nn, true, true, relb, sel, [] {}, [&](uint32_t lo) {
          uint64_t d1 = desc(lo | (512u << 16), HI128), d2 = desc(lo + 1024, HI64);
          #pragma unroll
          for (int kk = 0; kk < 4; kk++) if (kk < nk) {
            rs128<0, 1>(c1, f[kk].x, f[kk].y, f[kk].z, f[kk].w, d1, 128);
            rs32<0, 1>(c2, f[kk].x, f[kk].y, f[kk].z, f[kk].w, d2, 64);
          }
        }, [] {});
      };
      auto ldx = [&] {
        mbar_wait(bars + 8 * B_XRES, 0);
        #pragma unroll
        for (int i = 0; i < 5; i++)
          asm volatile("ldmatrix.sync.aligned.m8n8.x4.shared.b16 {%0,%1,%2,%3}, [%4];" : "=r"(xv[i].x), "=r"(xv[i].y), "=r"(xv[i].z), "=r"(xv[i].w)
                       : "r"(i < 4 ? xa + ((xs ^ (2 * i)) << 4) : xb) : "memory");
      };
      auto outp = [&](uint4 (&f)[5], uint4 (&fn)[5], bool first, bool fetch, bool rela, bool relb, auto extra) {
        PROFL(224 + wg * 10 + sidx); sidx++;
        stage(f, 5, fn, 5, fetch, rela, relb, 2, [&] { if (!fetch) ldx(); }, [&](uint32_t lo) {
          uint64_t db = desc(lo | (640u << 16), HI128);
          if (first) rs80<0, 0>(c, f[0].x, f[0].y, f[0].z, f[0].w, db, 128); else rs80<0, 1>(c, f[0].x, f[0].y, f[0].z, f[0].w, db, 128);
          #pragma unroll
          for (int kk = 1; kk < 5; kk++) rs80<0, 1>(c, f[kk].x, f[kk].y, f[kk].z, f[kk].w, db, 128);
        }, extra);
      };
      const int ntrip = role ? 5 : 3;
      PROFL(127 - wg);
      down(fa[0], 2, fa[1], 4, false, 0);
      #pragma unroll 1
      for (int m = 0;; m++) {
        PROFL(128 + wg * 20 + 3 * m);
        down(fa[1], 4, fa[2], 5, true, min(m, 2));
        if (m == ntrip) break;
        PROFC(129 + wg * 20 + 3 * m);
        down(fa[2], 4, fa[0], 4, true, m ? 2 : 0);
        PROFC(130 + wg * 20 + 3 * m);
        down(fa[0], 4, fa[1], 4, true, m ? 2 : 0);
      }
      uint32_t tag;
      asm volatile("ld.shared.u32 %0, [%1];" : "=r"(tag) : "r"(base + OFF_EP) : "memory");
      tag = (tag + 1) & 1;
      outp(fa[2], fa[0], true, true, true, true, [] {});
      pin<0, 64>(c1); pin<0, 16>(c2);
      PROFC(11 + wg * 16);
      outp(fa[0], fa[1], false, true, true, true, [&] {
        uint4* dst = g_p + (b * 8 + warp) * 160 + lane;
        auto put = [&](int i, const float* v) { stg_relaxed(dst + i * 32, (pack(v[0], v[1]) & ~1u) | tag, pack(v[2], v[3]), pack(v[4], v[5]), pack(v[6], v[7])); };
        #pragma unroll
        for (int i = 0; i < 4; i++) put(i, &c1[32 + 8 * i]);
        #pragma unroll
        for (int i = 0; i < 8; i++) { const float u = c2[i], v = c2[8 + i]; c2[i] = role ? v : u; c2[8 + i] = role ? u : v; }
        put(4, &c2[8]);
      });
      outp(fa[1], fa[2], false, true, true, true, [&] {
        #pragma unroll
        for (int i = 0; i < 20; i++) { kp[i] = i < 16 ? pack(c1[2 * i], c1[2 * i + 1]) : pack(c2[2 * i - 32], c2[2 * i - 31]); asm volatile("" : "+r"(kp[i])); }
      });
      const uint4* src = g_p + (mate * 8 + warp) * 160 + lane;
      auto recv = [&] {
        #pragma unroll
        for (int i = 0; i < 5; i++) pv[i] = ldg_relaxed(src + i * 32);
      };
      auto check = [&] {
        uint32_t bad = 0, n = 0;
        #pragma unroll 1
        do {
          #pragma unroll
          for (int i = 0; i < 5; i++)
            asm volatile("{\n.reg .pred p;\nsetp.ne.u32 p, %5, 0;\n@p ld.relaxed.gpu.global.v4.u32 {%0, %1, %2, %3}, [%4];\n}"
                         : "+r"(pv[i].x), "+r"(pv[i].y), "+r"(pv[i].z), "+r"(pv[i].w) : "l"(src + i * 32), "r"(bad) : "memory");
          bad = 0;
          #pragma unroll
          for (int i = 0; i < 5; i++) bad |= pv[i].x ^ tag;
          bad = __any_sync(0xffffffffu, bad & 1);
        } while (bad && ++n < (1u << 18));
        PROFL(12 + wg * 16);
      };
      auto gate = [&](int i0, int i1) {
        #pragma unroll
        for (int i = i0; i < i1; i++) {
          const uint4 v = pv[i / 4]; const int j = i & 3;
          const uint32_t h = hmul(hadd(kp[i], j == 0 ? v.x : j == 1 ? v.y : j == 2 ? v.z : v.w), 0x3f003f00u);
          uint32_t t;
          asm("tanh.approx.bf16x2 %0, %1;" : "=r"(t) : "r"(h));
          kp[i] = hfma(h, t, h);
          asm volatile("" : "+r"(kp[i]));
        }
      };
      outp(fa[2], fa[0], false, true, false, true, [] {});
      outp(fa[0], fa[1], false, true, false, false, [&] { if (RV == 4) recv(); });
      outp(fa[1], fa[2], false, true, false, false, [&] { if (RV == 5) recv(); });
      outp(fa[2], fa[0], false, true, false, false, [] {});
      outp(fa[0], fa[1], false, false, false, false, [&] { check(); gate(0, 20); mbar_wait(bars + 8 * B_XRES, 0); });
      wg_wait<0>();
      pin<0, 40>(c);
      PROFL(13 + wg * 16);
      #pragma unroll
      for (int i = 0; i < 5; i++) {
        stsm4(i < 4 ? xa + ((xs ^ (2 * i)) << 4) : xb, hfma(pack(c[8 * i], c[8 * i + 1]), kp[4 * i], xv[i].x), hfma(pack(c[8 * i + 2], c[8 * i + 3]), kp[4 * i + 1], xv[i].y),
              hfma(pack(c[8 * i + 4], c[8 * i + 5]), kp[4 * i + 2], xv[i].z), hfma(pack(c[8 * i + 6], c[8 * i + 7]), kp[4 * i + 3], xv[i].w));
      }
      asm volatile("fence.proxy.async.shared::cta;" ::: "memory");
      __syncwarp();
      if (elect()) {
        asm volatile("cp.async.bulk.tensor.2d.global.shared::cta.bulk_group [%0, {%1, %2}], [%3];" :: "l"(&M.oa), "r"(cl), "r"(rb * 128 + warp * 16), "r"(base + OFF_AUX + warp * 2048) : "memory");
        asm volatile("cp.async.bulk.tensor.2d.global.shared::cta.bulk_group [%0, {%1, %2}], [%3];" :: "l"(&M.ob), "r"(ch + 16 * role), "r"(rb * 128 + warp * 16), "r"(base + OFF_AUX + 16384 + warp * 512) : "memory");
        asm volatile("cp.async.bulk.commit_group;" ::: "memory");
        asm volatile("cp.async.bulk.wait_group.read 0;" ::: "memory");
      }
      PROFL(14 + wg * 16);
    }
    PROFEND();
    if (blockIdx.y == 0) return;
  }
PUBLISHER:
  {
    const int lane = tid & 31;
      const int w = warp - 10, nev = role ? 4 : 5;
      unsigned ep = 0;
      if (lane == 0) {
        if (w) {
          ep = *(volatile unsigned*)&g_epoch[b];
          *(volatile unsigned*)&g_epoch[b] = ep + 1;
          asm volatile("st.shared.u32 [%0], %1;" :: "r"(base + OFF_EP), "r"(ep) : "memory");
          mbar_arrive(bars + 8 * B_EP);
        } else {
          mbar_wait(bars + 8 * B_EP, 0);
          asm volatile("ld.shared.u32 %0, [%1];" : "=r"(ep) : "r"(base + OFF_EP) : "memory");
        }
      }
      ep = __shfl_sync(0xffffffffu, ep, 0);
      if (w && lane < 30) reinterpret_cast<float4*>(g_kv + ((ep + 1) & 1) * 15360 + b * 120)[lane] = make_float4(0.f, 0.f, 0.f, 0.f);
      const float* kvs = g_kv + ((ep & 1) * 8 + g) * 1920;
      if (elect()) {
        mbar_wait(bars + 8 * (B_EV + w * 5), 0);
        asm volatile("cp.reduce.async.bulk.global.shared::cta.bulk_group.add.f32 [%0], [%1], 7680;" :: "l"(kvs), "r"(base + (6 + w) * SLOT + 12288) : "memory");
        asm volatile("cp.async.bulk.commit_group;" ::: "memory");
        asm volatile("cp.async.bulk.wait_group.read 0;" ::: "memory");
        asm volatile("mbarrier.arrive.shared::cta.b64 _, [%0], 4;" :: "r"(bars + 8 * (B_EMPTY + 6 + w)) : "memory");
        asm volatile("cp.async.bulk.wait_group 0;" ::: "memory");
        asm volatile("fence.proxy.async.global;" ::: "memory");
        asm volatile("red.release.gpu.global.add.u32 [%0], 1;" :: "l"(&g_cnt[(C_KV + g) * 8]) : "memory");
        if (w) PROFT(52);
        poll_ge(&g_cnt[(C_KV + g) * 8], (ep + 1) * 32);
        if (w) PROFT(53);
      }
      __syncwarp();
      {
        const uint32_t kb = base + OFF_AUX;
        const int eq = lane % 6, dpo = lane / 6;
        #pragma unroll 1
        for (int i = lane + 32 * w; i < 880; i += 64) sts128(kb + i * 16, 0, 0, 0, 0);
        asm volatile("bar.sync 5, 64;" ::: "memory");
        if (lane < 30) {
          #pragma unroll 1
          for (int i = 4 * w; i < 4 * w + 4; i++) {
            const int h = i >> 1, d = 10 * i + 2 * dpo, n = eq < 5 ? 20 * h + 4 * eq : 80 + h;
            const uint4 u = ldg_relaxed(kvs + d * 24 + eq * 4), v = ldg_relaxed(kvs + d * 24 + 24 + eq * 4);
            const uint32_t ad = kb + (d >> 4) * 2816 + n * 32 + ((((d >> 3) ^ (n >> 2)) & 1) << 4) + (d & 7) * 2;
            const float zu = eq < 5 ? 0.f : __uint_as_float(u.y), zv = eq < 5 ? 0.f : __uint_as_float(v.y);
            asm volatile("st.shared.u32 [%0], %1;" :: "r"(ad), "r"(pack(__uint_as_float(u.x) + zu, __uint_as_float(v.x) + zv)) : "memory");
            if (eq < 5) {
              asm volatile("st.shared.u32 [%0], %1;" :: "r"(ad + 32), "r"(pack(__uint_as_float(u.y), __uint_as_float(v.y))) : "memory");
              asm volatile("st.shared.u32 [%0], %1;" :: "r"(ad + 64), "r"(pack(__uint_as_float(u.z), __uint_as_float(v.z))) : "memory");
              asm volatile("st.shared.u32 [%0], %1;" :: "r"(ad + 96), "r"(pack(__uint_as_float(u.w), __uint_as_float(v.w))) : "memory");
            }
          }
        }
        asm volatile("fence.proxy.async.shared::cta;" ::: "memory");
        __syncwarp();
        if (lane == 0) { mbar_arrive(bars + 8 * B_KVRDY); if (w) PROFT(46); }
      }
      if (lane == 0) {
        if (!w) {
          #pragma unroll 1
          for (int e = 1; e < nev; e++) {
            const int c = e == nev - 1 ? C_O + 2 * rb + role : C_H + rb * 3 + (e - 1);
            mbar_wait(bars + 8 * (B_EV + e), 0);
            mbar_wait(bars + 8 * (B_EV + 5 + e), 0);
            asm volatile("red.release.gpu.global.add.u32 [%0], 1;" :: "l"(&g_cnt[c * 8]) : "memory");
          }
        } else {
          #pragma unroll 1
          for (int i = 0; i < 4; i++) {
            poll_ge(&g_cnt[(i < 2 ? C_H + rb * 3 + 1 + i - role : C_O + 2 * rb + 3 - i) * 8], (ep + 1) * (i == 0 || (i == 1 && role) ? 8 : 4));
            mbar_arrive(bars + 8 * (B_OK + i));
          }
        }
      }
    PROFEND();
  }
}

typedef CUresult (*EncFn)(CUtensorMap*, CUtensorMapDataType, cuuint32_t, void*, const cuuint64_t*, const cuuint64_t*, const cuuint32_t*,
                          const cuuint32_t*, CUtensorMapInterleave, CUtensorMapSwizzle, CUtensorMapL2promotion, CUtensorMapFloatOOBfill);

CUtensorMap make_map(EncFn enc, const void* p, int rows, int cols, int box_r, int box_c, CUtensorMapSwizzle swz) {
  CUtensorMap m;
  cuuint64_t dims[2] = {(cuuint64_t)cols, (cuuint64_t)rows};
  cuuint64_t str[1] = {(cuuint64_t)cols * 2};
  cuuint32_t box[2] = {(cuuint32_t)box_c, (cuuint32_t)box_r};
  cuuint32_t es[2] = {1, 1};
  enc(&m, CU_TENSOR_MAP_DATA_TYPE_BFLOAT16, 2, const_cast<void*>(p), dims, str, box, es, CU_TENSOR_MAP_INTERLEAVE_NONE, swz,
      CU_TENSOR_MAP_L2_PROMOTION_L2_128B, CU_TENSOR_MAP_FLOAT_OOB_FILL_NONE);
  return m;
}

}

extern "C" void kernel_launch(void* const* d_in, const int* in_sizes, int n_in, void* d_out, int out_size) {
  (void)in_sizes; (void)n_in; (void)out_size;
  static EncFn enc = nullptr;
  if (!enc) {
    cudaDriverEntryPointQueryResult q;
    cudaGetDriverEntryPoint("cuTensorMapEncodeTiled", (void**)&enc, cudaEnableDefault, &q);
    cudaFuncSetAttribute(fused_kernel, cudaFuncAttributeMaxDynamicSharedMemorySize, SMEM_BYTES);
  }
  Maps M;
  {
    cuuint64_t dims[3] = {64, (cuuint64_t)S_, 10}, str[2] = {D_ * 2, 128};
    cuuint32_t box[3] = {64, 64, 2}, es[3] = {1, 1, 1};
    enc(&M.x, CU_TENSOR_MAP_DATA_TYPE_BFLOAT16, 3, d_in[0], dims, str, box, es, CU_TENSOR_MAP_INTERLEAVE_NONE, CU_TENSOR_MAP_SWIZZLE_128B,
        CU_TENSOR_MAP_L2_PROMOTION_L2_128B, CU_TENSOR_MAP_FLOAT_OOB_FILL_NONE);
  }
  M.qkv64 = make_map(enc, d_in[1], D_, 3 * D_, 80, 64, CU_TENSOR_MAP_SWIZZLE_128B);
  M.qkv16 = make_map(enc, d_in[1], D_, 3 * D_, 80, 16, CU_TENSOR_MAP_SWIZZLE_128B);
  M.woa = make_map(enc, d_in[2], D_, D_, 80, 64, CU_TENSOR_MAP_SWIZZLE_128B);
  M.wob = make_map(enc, d_in[2], D_, D_, 80, 16, CU_TENSOR_MAP_SWIZZLE_128B);
  M.w1a = make_map(enc, d_in[4], D_, F_, 80, 64, CU_TENSOR_MAP_SWIZZLE_128B);
  M.w1b = make_map(enc, d_in[4], D_, F_, 80, 32, CU_TENSOR_MAP_SWIZZLE_128B);
  M.w3a = make_map(enc, d_in[5], D_, F_, 80, 64, CU_TENSOR_MAP_SWIZZLE_128B);
  M.w3b = make_map(enc, d_in[5], D_, F_, 80, 32, CU_TENSOR_MAP_SWIZZLE_128B);
  M.w1c = make_map(enc, d_in[4], D_, F_, 80, 48, CU_TENSOR_MAP_SWIZZLE_128B);
  M.w3c = make_map(enc, d_in[5], D_, F_, 80, 48, CU_TENSOR_MAP_SWIZZLE_128B);
  M.w2a = make_map(enc, d_in[6], F_, D_, 64, 64, CU_TENSOR_MAP_SWIZZLE_128B);
  M.w2b = make_map(enc, d_in[6], F_, D_, 64, 32, CU_TENSOR_MAP_SWIZZLE_64B);
  M.xa = make_map(enc, d_in[0], S_, D_, 128, 64, CU_TENSOR_MAP_SWIZZLE_128B);
  M.xb = make_map(enc, d_in[0], S_, D_, 128, 16, CU_TENSOR_MAP_SWIZZLE_32B);
  M.oa = make_map(enc, d_out, S_, D_, 16, 64, CU_TENSOR_MAP_SWIZZLE_128B);
  M.ob = make_map(enc, d_out, S_, D_, 16, 16, CU_TENSOR_MAP_SWIZZLE_32B);
  fused_kernel<<<128, 384, SMEM_BYTES>>>(M);
}
```

```cpp
#include <cuda_runtime.h>
#include <cuda_bf16.h>
#include <cuda.h>
#include <stdint.h>

namespace {

constexpr int S_ = 2048, D_ = 640, F_ = 1728;
constexpr int NSLOT = 10, SLOT = 20480;
constexpr int OFF_AUX = NSLOT * SLOT;
constexpr int OFF_BAR = OFF_AUX + 24576;
constexpr int B_EMPTY = 10, B_XFULL = 20, B_XFREE = 30, B_EV = 33, B_KVRDY = 43, B_EP = 44, B_AUXF = 46, B_OK = 47;
constexpr int OFF_EP = OFF_BAR + 58 * 8;
constexpr int OFF_PROF = OFF_EP + 16;
constexpr int SMEM_BYTES = OFF_PROF + 1024;
#define S0 6
#define DLY 20
#define MAP 3
constexpr int NY = 66;

__device__ uint4 g_h[16 * 108 * 256];
__device__ uint4 g_o[16 * 40 * 256];
__device__ uint4 g_p[128 * 8 * 5 * 32];
__device__ float g_kv[2 * 8 * 2 * 960];
__device__ unsigned g_cnt[128 * 8];
__device__ unsigned g_epoch[128];
constexpr int C_H = 0, C_O = 48, C_KV = 80;

#define PROFC(i)
#define PROFT(i)
#define PROFT_(i)
#define TWAIT(bar, ph, i) mbar_wait(bar, ph)
#define PROFL(i)
#define PROFEND()

__device__ __forceinline__ uint32_t smem_u32(const void* p) { return (uint32_t)__cvta_generic_to_shared(p); }
__device__ __forceinline__ void mbar_init(uint32_t bar, uint32_t cnt) { asm volatile("mbarrier.init.shared::cta.b64 [%0], %1;" :: "r"(bar), "r"(cnt) : "memory"); }
__device__ __forceinline__ void mbar_expect(uint32_t bar, uint32_t bytes) { asm volatile("mbarrier.arrive.expect_tx.shared::cta.b64 _, [%0], %1;" :: "r"(bar), "r"(bytes) : "memory"); }
__device__ __forceinline__ void mbar_arrive(uint32_t bar) { asm volatile("mbarrier.arrive.shared::cta.b64 _, [%0];" :: "r"(bar) : "memory"); }
__device__ __forceinline__ void mbar_wait(uint32_t bar, uint32_t parity) {
  asm volatile("{\n.reg .pred p;\nLOOP:\nmbarrier.try_wait.parity.shared::cta.b64 p, [%0], %1;\n@!p bra.uni LOOP;\n}" :: "r"(bar), "r"(parity) : "memory");
}
__device__ __forceinline__ void poll_ge(const unsigned* p, unsigned target) {
  #pragma unroll 1
  for (uint32_t n = 0; n < (1u << 20); n++) {
    unsigned v;
    asm volatile("ld.acquire.gpu.global.u32 %0, [%1];" : "=r"(v) : "l"(p) : "memory");
    if ((int)(v - target) >= 0) break;
  }
}
__device__ __forceinline__ void tma2d(uint32_t dst, const CUtensorMap* m, int c0, int c1, uint32_t bar) {
  asm volatile("cp.async.bulk.tensor.2d.shared::cluster.global.mbarrier::complete_tx::bytes [%0], [%1, {%3, %4}], [%2];"
    :: "r"(dst), "l"(m), "r"(bar), "r"(c0), "r"(c1) : "memory");
}
__device__ __forceinline__ void tma3d(uint32_t dst, const CUtensorMap* m, int c0, int c1, int c2, uint32_t bar) {
  asm volatile("cp.async.bulk.tensor.3d.shared::cluster.global.mbarrier::complete_tx::bytes [%0], [%1, {%3, %4, %5}], [%2];"
    :: "r"(dst), "l"(m), "r"(bar), "r"(c0), "r"(c1), "r"(c2) : "memory");
}
__device__ __forceinline__ void bulk(uint32_t dst, const void* src, uint32_t bytes, uint32_t bar) {
  asm volatile("cp.async.bulk.shared::cluster.global.mbarrier::complete_tx::bytes [%0], [%1], %2, [%3];" :: "r"(dst), "l"(src), "r"(bytes), "r"(bar) : "memory");
}
__device__ __forceinline__ void wg_fence() { asm volatile("wgmma.fence.sync.aligned;" ::: "memory"); }
__device__ __forceinline__ void wg_commit() { asm volatile("wgmma.commit_group.sync.aligned;" ::: "memory"); }
template<int N> __device__ __forceinline__ void wg_wait() { asm volatile("wgmma.wait_group.sync.aligned %0;" :: "n"(N) : "memory"); }
template<int O, int N, int L> __device__ __forceinline__ void pin(float (&d)[L]) {
  #pragma unroll
  for (int i = 0; i < N; i++) asm volatile("" : "+f"(d[O + i]) :: "memory");
}
__device__ __forceinline__ int fresh_tid() { int t; asm volatile("mov.u32 %0, %%tid.x;" : "=r"(t)); return t; }
__device__ __forceinline__ uint4 lds128(uint32_t a) { uint4 v; asm volatile("ld.shared.v4.u32 {%0,%1,%2,%3}, [%4];" : "=r"(v.x), "=r"(v.y), "=r"(v.z), "=r"(v.w) : "r"(a) : "memory"); return v; }
__device__ __forceinline__ uint4 ldg_relaxed(const void* p) {
  uint4 v;
  asm volatile("ld.relaxed.gpu.global.v4.u32 {%0, %1, %2, %3}, [%4];" : "=r"(v.x), "=r"(v.y), "=r"(v.z), "=r"(v.w) : "l"(p) : "memory");
  return v;
}
__device__ __forceinline__ void stg_relaxed(void* p, uint32_t x, uint32_t y, uint32_t z, uint32_t w) {
  asm volatile("st.relaxed.gpu.global.v4.u32 [%0], {%1, %2, %3, %4};" :: "l"(p), "r"(x), "r"(y), "r"(z), "r"(w) : "memory");
}
__device__ __forceinline__ void sts128(uint32_t a, uint32_t x, uint32_t y, uint32_t z, uint32_t w) {
  asm volatile("st.shared.v4.u32 [%0], {%1,%2,%3,%4};" :: "r"(a), "r"(x), "r"(y), "r"(z), "r"(w) : "memory");
}
__device__ __forceinline__ void stsm4(uint32_t a, uint32_t r0, uint32_t r1, uint32_t r2, uint32_t r3) {
  asm volatile("stmatrix.sync.aligned.m8n8.x4.shared.b16 [%0], {%1,%2,%3,%4};" :: "r"(a), "r"(r0), "r"(r1), "r"(r2), "r"(r3) : "memory");
}
__device__ __forceinline__ uint32_t pack(float lo, float hi) { uint32_t r; asm("cvt.rn.bf16x2.f32 %0, %1, %2;" : "=r"(r) : "f"(hi), "f"(lo)); return r; }
__device__ __forceinline__ float blo(uint32_t v) { return __uint_as_float(v << 16); }
__device__ __forceinline__ float bhi(uint32_t v) { return __uint_as_float(v & 0xffff0000u); }
__device__ __forceinline__ float ex2(float x) { float y; asm("ex2.approx.ftz.f32 %0, %1;" : "=f"(y) : "f"(x)); return y; }
__device__ __forceinline__ float rcp(float x) { float y; asm("rcp.approx.ftz.f32 %0, %1;" : "=f"(y) : "f"(x)); return y; }
__device__ __forceinline__ float tanh_(float x) { float y; asm("tanh.approx.f32 %0, %1;" : "=f"(y) : "f"(x)); return y; }
__device__ __forceinline__ uint32_t hadd(uint32_t a, uint32_t b) { uint32_t r; asm("add.rn.bf16x2 %0, %1, %2;" : "=r"(r) : "r"(a), "r"(b)); return r; }
__device__ __forceinline__ uint32_t hmul(uint32_t a, uint32_t b) { uint32_t r; asm("mul.rn.bf16x2 %0, %1, %2;" : "=r"(r) : "r"(a), "r"(b)); return r; }
__device__ __forceinline__ uint32_t hfma(uint32_t a, uint32_t b, uint32_t c) { uint32_t r; asm("fma.rn.bf16x2 %0, %1, %2, %3;" : "=r"(r) : "r"(a), "r"(b), "r"(c)); return r; }
__device__ __forceinline__ void mma16(float (&d)[4], uint32_t a0, uint32_t a1, uint32_t a2, uint32_t a3, uint32_t b0, uint32_t b1) {
  asm volatile("mma.sync.aligned.m16n8k16.row.col.f32.bf16.bf16.f32 {%0,%1,%2,%3}, {%4,%5,%6,%7}, {%8,%9}, {%0,%1,%2,%3};"
               : "+f"(d[0]), "+f"(d[1]), "+f"(d[2]), "+f"(d[3]) : "r"(a0), "r"(a1), "r"(a2), "r"(a3), "r"(b0), "r"(b1));
}
constexpr float LOG2E = 1.4426950408889634f;
template<int SCALED> __device__ __forceinline__ uint32_t phi2(float u, float v, float r, float k) {
  const float s = SCALED ? r : 1.f, e = 1e-6f * s;
  return pack(fmaf(u > 0.f ? fmaf(u, r, 1.f) : ex2(u * k), s, e), fmaf(v > 0.f ? fmaf(v, r, 1.f) : ex2(v * k), s, e));
}
__device__ __forceinline__ float silu2(float h) { return fmaf(h, tanh_(h), h); }

template<int O, int SD, int L> __device__ __forceinline__ void rs96(float (&d)[L], uint32_t a0, uint32_t a1, uint32_t a2, uint32_t a3, uint64_t& db, uint32_t st) {
  if (SD) asm volatile("{\n.reg .pred p;\nsetp.ne.b32 p, 1, 0;\n"
    "wgmma.mma_async.sync.aligned.m64n96k16.f32.bf16.bf16 {%0, %1, %2, %3, %4, %5, %6, %7, %8, %9, %10, %11, %12, %13, %14, %15, %16, %17, %18, %19, %20, %21, %22, %23, %24, %25, %26, %27, %28, %29, %30, %31, %32, %33, %34, %35, %36, %37, %38, %39, %40, %41, %42, %43, %44, %45, %46, %47}, {%48, %49, %50, %51}, %52, p, 1, 1, 1;\n}\n"
    : "+f"(d[O + 0]), "+f"(d[O + 1]), "+f"(d[O + 2]), "+f"(d[O + 3]), "+f"(d[O + 4]), "+f"(d[O + 5]), "+f"(d[O + 6]), "+f"(d[O + 7]), "+f"(d[O + 8]), "+f"(d[O + 9]), "+f"(d[O + 10]), "+f"(d[O + 11]), "+f"(d[O + 12]), "+f"(d[O + 13]), "+f"(d[O + 14]), "+f"(d[O + 15]), "+f"(d[O + 16]), "+f"(d[O + 17]), "+f"(d[O + 18]), "+f"(d[O + 19]), "+f"(d[O + 20]), "+f"(d[O + 21]), "+f"(d[O + 22]), "+f"(d[O + 23]), "+f"(d[O + 24]), "+f"(d[O + 25]), "+f"(d[O + 26]), "+f"(d[O + 27]), "+f"(d[O + 28]), "+f"(d[O + 29]), "+f"(d[O + 30]), "+f"(d[O + 31]), "+f"(d[O + 32]), "+f"(d[O + 33]), "+f"(d[O + 34]), "+f"(d[O + 35]), "+f"(d[O + 36]), "+f"(d[O + 37]), "+f"(d[O + 38]), "+f"(d[O + 39]), "+f"(d[O + 40]), "+f"(d[O + 41]), "+f"(d[O + 42]), "+f"(d[O + 43]), "+f"(d[O + 44]), "+f"(d[O + 45]), "+f"(d[O + 46]), "+f"(d[O + 47])
    : "r"(a0), "r"(a1), "r"(a2), "r"(a3), "l"(db));
  else asm volatile("{\n.reg .pred p;\nsetp.ne.b32 p, 0, 0;\n"
    "wgmma.mma_async.sync.aligned.m64n96k16.f32.bf16.bf16 {%0, %1, %2, %3, %4, %5, %6, %7, %8, %9, %10, %11, %12, %13, %14, %15, %16, %17, %18, %19, %20, %21, %22, %23, %24, %25, %26, %27, %28, %29, %30, %31, %32, %33, %34, %35, %36, %37, %38, %39, %40, %41, %42, %43, %44, %45, %46, %47}, {%48, %49, %50, %51}, %52, p, 1, 1, 1;\n}\n"
    : "=f"(d[O + 0]), "=f"(d[O + 1]), "=f"(d[O + 2]), "=f"(d[O + 3]), "=f"(d[O + 4]), "=f"(d[O + 5]), "=f"(d[O + 6]), "=f"(d[O + 7]), "=f"(d[O + 8]), "=f"(d[O + 9]), "=f"(d[O + 10]), "=f"(d[O + 11]), "=f"(d[O + 12]), "=f"(d[O + 13]), "=f"(d[O + 14]), "=f"(d[O + 15]), "=f"(d[O + 16]), "=f"(d[O + 17]), "=f"(d[O + 18]), "=f"(d[O + 19]), "=f"(d[O + 20]), "=f"(d[O + 21]), "=f"(d[O + 22]), "=f"(d[O + 23]), "=f"(d[O + 24]), "=f"(d[O + 25]), "=f"(d[O + 26]), "=f"(d[O + 27]), "=f"(d[O + 28]), "=f"(d[O + 29]), "=f"(d[O + 30]), "=f"(d[O + 31]), "=f"(d[O + 32]), "=f"(d[O + 33]), "=f"(d[O + 34]), "=f"(d[O + 35]), "=f"(d[O + 36]), "=f"(d[O + 37]), "=f"(d[O + 38]), "=f"(d[O + 39]), "=f"(d[O + 40]), "=f"(d[O + 41]), "=f"(d[O + 42]), "=f"(d[O + 43]), "=f"(d[O + 44]), "=f"(d[O + 45]), "=f"(d[O + 46]), "=f"(d[O + 47])
    : "r"(a0), "r"(a1), "r"(a2), "r"(a3), "l"(db));
  db += st;
}
template<int O, int SD, int L> __device__ __forceinline__ void rs48(float (&d)[L], uint32_t a0, uint32_t a1, uint32_t a2, uint32_t a3, uint64_t& db, uint32_t st) {
  if (SD) asm volatile("{\n.reg .pred p;\nsetp.ne.b32 p, 1, 0;\n"
    "wgmma.mma_async.sync.aligned.m64n48k16.f32.bf16.bf16 {%0, %1, %2, %3, %4, %5, %6, %7, %8, %9, %10, %11, %12, %13, %14, %15, %16, %17, %18, %19, %20, %21, %22, %23}, {%24, %25, %26, %27}, %28, p, 1, 1, 1;\n}\n"
    : "+f"(d[O + 0]), "+f"(d[O + 1]), "+f"(d[O + 2]), "+f"(d[O + 3]), "+f"(d[O + 4]), "+f"(d[O + 5]), "+f"(d[O + 6]), "+f"(d[O + 7]), "+f"(d[O + 8]), "+f"(d[O + 9]), "+f"(d[O + 10]), "+f"(d[O + 11]), "+f"(d[O + 12]), "+f"(d[O + 13]), "+f"(d[O + 14]), "+f"(d[O + 15]), "+f"(d[O + 16]), "+f"(d[O + 17]), "+f"(d[O + 18]), "+f"(d[O + 19]), "+f"(d[O + 20]), "+f"(d[O + 21]), "+f"(d[O + 22]), "+f"(d[O + 23])
    : "r"(a0), "r"(a1), "r"(a2), "r"(a3), "l"(db));
  else asm volatile("{\n.reg .pred p;\nsetp.ne.b32 p, 0, 0;\n"
    "wgmma.mma_async.sync.aligned.m64n48k16.f32.bf16.bf16 {%0, %1, %2, %3, %4, %5, %6, %7, %8, %9, %10, %11, %12, %13, %14, %15, %16, %17, %18, %19, %20, %21, %22, %23}, {%24, %25, %26, %27}, %28, p, 1, 1, 1;\n}\n"
    : "=f"(d[O + 0]), "=f"(d[O + 1]), "=f"(d[O + 2]), "=f"(d[O + 3]), "=f"(d[O + 4]), "=f"(d[O + 5]), "=f"(d[O + 6]), "=f"(d[O + 7]), "=f"(d[O + 8]), "=f"(d[O + 9]), "=f"(d[O + 10]), "=f"(d[O + 11]), "=f"(d[O + 12]), "=f"(d[O + 13]), "=f"(d[O + 14]), "=f"(d[O + 15]), "=f"(d[O + 16]), "=f"(d[O + 17]), "=f"(d[O + 18]), "=f"(d[O + 19]), "=f"(d[O + 20]), "=f"(d[O + 21]), "=f"(d[O + 22]), "=f"(d[O + 23])
    : "r"(a0), "r"(a1), "r"(a2), "r"(a3), "l"(db));
  db += st;
}
template<int O, int SD, int L> __device__ __forceinline__ void rs128(float (&d)[L], uint32_t a0, uint32_t a1, uint32_t a2, uint32_t a3, uint64_t& db, uint32_t st) {
  if (SD) asm volatile("{\n.reg .pred p;\nsetp.ne.b32 p, 1, 0;\n"
    "wgmma.mma_async.sync.aligned.m64n128k16.f32.bf16.bf16 {%0, %1, %2, %3, %4, %5, %6, %7, %8, %9, %10, %11, %12, %13, %14, %15, %16, %17, %18, %19, %20, %21, %22, %23, %24, %25, %26, %27, %28, %29, %30, %31, %32, %33, %34, %35, %36, %37, %38, %39, %40, %41, %42, %43, %44, %45, %46, %47, %48, %49, %50, %51, %52, %53, %54, %55, %56, %57, %58, %59, %60, %61, %62, %63}, {%64, %65, %66, %67}, %68, p, 1, 1, 1;\n}\n"
    : "+f"(d[O + 0]), "+f"(d[O + 1]), "+f"(d[O + 2]), "+f"(d[O + 3]), "+f"(d[O + 4]), "+f"(d[O + 5]), "+f"(d[O + 6]), "+f"(d[O + 7]), "+f"(d[O + 8]), "+f"(d[O + 9]), "+f"(d[O + 10]), "+f"(d[O + 11]), "+f"(d[O + 12]), "+f"(d[O + 13]), "+f"(d[O + 14]), "+f"(d[O + 15]), "+f"(d[O + 16]), "+f"(d[O + 17]), "+f"(d[O + 18]), "+f"(d[O + 19]), "+f"(d[O + 20]), "+f"(d[O + 21]), "+f"(d[O + 22]), "+f"(d[O + 23]), "+f"(d[O + 24]), "+f"(d[O + 25]), "+f"(d[O + 26]), "+f"(d[O + 27]), "+f"(d[O + 28]), "+f"(d[O + 29]), "+f"(d[O + 30]), "+f"(d[O + 31]), "+f"(d[O + 32]), "+f"(d[O + 33]), "+f"(d[O + 34]), "+f"(d[O + 35]), "+f"(d[O + 36]), "+f"(d[O + 37]), "+f"(d[O + 38]), "+f"(d[O + 39]), "+f"(d[O + 40]), "+f"(d[O + 41]), "+f"(d[O + 42]), "+f"(d[O + 43]), "+f"(d[O + 44]), "+f"(d[O + 45]), "+f"(d[O + 46]), "+f"(d[O + 47]), "+f"(d[O + 48]), "+f"(d[O + 49]), "+f"(d[O + 50]), "+f"(d[O + 51]), "+f"(d[O + 52]), "+f"(d[O + 53]), "+f"(d[O + 54]), "+f"(d[O + 55]), "+f"(d[O + 56]), "+f"(d[O + 57]), "+f"(d[O + 58]), "+f"(d[O + 59]), "+f"(d[O + 60]), "+f"(d[O + 61]), "+f"(d[O + 62]), "+f"(d[O + 63])
    : "r"(a0), "r"(a1), "r"(a2), "r"(a3), "l"(db));
  else asm volatile("{\n.reg .pred p;\nsetp.ne.b32 p, 0, 0;\n"
    "wgmma.mma_async.sync.aligned.m64n128k16.f32.bf16.bf16 {%0, %1, %2, %3, %4, %5, %6, %7, %8, %9, %10, %11, %12, %13, %14, %15, %16, %17, %18, %19, %20, %21, %22, %23, %24, %25, %26, %27, %28, %29, %30, %31, %32, %33, %34, %35, %36, %37, %38, %39, %40, %41, %42, %43, %44, %45, %46, %47, %48, %49, %50, %51, %52, %53, %54, %55, %56, %57, %58, %59, %60, %61, %62, %63}, {%64, %65, %66, %67}, %68, p, 1, 1, 1;\n}\n"
    : "=f"(d[O + 0]), "=f"(d[O + 1]), "=f"(d[O + 2]), "=f"(d[O + 3]), "=f"(d[O + 4]), "=f"(d[O + 5]), "=f"(d[O + 6]), "=f"(d[O + 7]), "=f"(d[O + 8]), "=f"(d[O + 9]), "=f"(d[O + 10]), "=f"(d[O + 11]), "=f"(d[O + 12]), "=f"(d[O + 13]), "=f"(d[O + 14]), "=f"(d[O + 15]), "=f"(d[O + 16]), "=f"(d[O + 17]), "=f"(d[O + 18]), "=f"(d[O + 19]), "=f"(d[O + 20]), "=f"(d[O + 21]), "=f"(d[O + 22]), "=f"(d[O + 23]), "=f"(d[O + 24]), "=f"(d[O + 25]), "=f"(d[O + 26]), "=f"(d[O + 27]), "=f"(d[O + 28]), "=f"(d[O + 29]), "=f"(d[O + 30]), "=f"(d[O + 31]), "=f"(d[O + 32]), "=f"(d[O + 33]), "=f"(d[O + 34]), "=f"(d[O + 35]), "=f"(d[O + 36]), "=f"(d[O + 37]), "=f"(d[O + 38]), "=f"(d[O + 39]), "=f"(d[O + 40]), "=f"(d[O + 41]), "=f"(d[O + 42]), "=f"(d[O + 43]), "=f"(d[O + 44]), "=f"(d[O + 45]), "=f"(d[O + 46]), "=f"(d[O + 47]), "=f"(d[O + 48]), "=f"(d[O + 49]), "=f"(d[O + 50]), "=f"(d[O + 51]), "=f"(d[O + 52]), "=f"(d[O + 53]), "=f"(d[O + 54]), "=f"(d[O + 55]), "=f"(d[O + 56]), "=f"(d[O + 57]), "=f"(d[O + 58]), "=f"(d[O + 59]), "=f"(d[O + 60]), "=f"(d[O + 61]), "=f"(d[O + 62]), "=f"(d[O + 63])
    : "r"(a0), "r"(a1), "r"(a2), "r"(a3), "l"(db));
  db += st;
}
template<int O, int SD, int L> __device__ __forceinline__ void rs32(float (&d)[L], uint32_t a0, uint32_t a1, uint32_t a2, uint32_t a3, uint64_t& db, uint32_t st) {
  if (SD) asm volatile("{\n.reg .pred p;\nsetp.ne.b32 p, 1, 0;\n"
    "wgmma.mma_async.sync.aligned.m64n32k16.f32.bf16.bf16 {%0, %1, %2, %3, %4, %5, %6, %7, %8, %9, %10, %11, %12, %13, %14, %15}, {%16, %17, %18, %19}, %20, p, 1, 1, 1;\n}\n"
    : "+f"(d[O + 0]), "+f"(d[O + 1]), "+f"(d[O + 2]), "+f"(d[O + 3]), "+f"(d[O + 4]), "+f"(d[O + 5]), "+f"(d[O + 6]), "+f"(d[O + 7]), "+f"(d[O + 8]), "+f"(d[O + 9]), "+f"(d[O + 10]), "+f"(d[O + 11]), "+f"(d[O + 12]), "+f"(d[O + 13]), "+f"(d[O + 14]), "+f"(d[O + 15])
    : "r"(a0), "r"(a1), "r"(a2), "r"(a3), "l"(db));
  else asm volatile("{\n.reg .pred p;\nsetp.ne.b32 p, 0, 0;\n"
    "wgmma.mma_async.sync.aligned.m64n32k16.f32.bf16.bf16 {%0, %1, %2, %3, %4, %5, %6, %7, %8, %9, %10, %11, %12, %13, %14, %15}, {%16, %17, %18, %19}, %20, p, 1, 1, 1;\n}\n"
    : "=f"(d[O + 0]), "=f"(d[O + 1]), "=f"(d[O + 2]), "=f"(d[O + 3]), "=f"(d[O + 4]), "=f"(d[O + 5]), "=f"(d[O + 6]), "=f"(d[O + 7]), "=f"(d[O + 8]), "=f"(d[O + 9]), "=f"(d[O + 10]), "=f"(d[O + 11]), "=f"(d[O + 12]), "=f"(d[O + 13]), "=f"(d[O + 14]), "=f"(d[O + 15])
    : "r"(a0), "r"(a1), "r"(a2), "r"(a3), "l"(db));
  db += st;
}
template<int O, int SD, int L> __device__ __forceinline__ void rs80(float (&d)[L], uint32_t a0, uint32_t a1, uint32_t a2, uint32_t a3, uint64_t& db, uint32_t st) {
  if (SD) asm volatile("{\n.reg .pred p;\nsetp.ne.b32 p, 1, 0;\n"
    "wgmma.mma_async.sync.aligned.m64n80k16.f32.bf16.bf16 {%0, %1, %2, %3, %4, %5, %6, %7, %8, %9, %10, %11, %12, %13, %14, %15, %16, %17, %18, %19, %20, %21, %22, %23, %24, %25, %26, %27, %28, %29, %30, %31, %32, %33, %34, %35, %36, %37, %38, %39}, {%40, %41, %42, %43}, %44, p, 1, 1, 1;\n}\n"
    : "+f"(d[O + 0]), "+f"(d[O + 1]), "+f"(d[O + 2]), "+f"(d[O + 3]), "+f"(d[O + 4]), "+f"(d[O + 5]), "+f"(d[O + 6]), "+f"(d[O + 7]), "+f"(d[O + 8]), "+f"(d[O + 9]), "+f"(d[O + 10]), "+f"(d[O + 11]), "+f"(d[O + 12]), "+f"(d[O + 13]), "+f"(d[O + 14]), "+f"(d[O + 15]), "+f"(d[O + 16]), "+f"(d[O + 17]), "+f"(d[O + 18]), "+f"(d[O + 19]), "+f"(d[O + 20]), "+f"(d[O + 21]), "+f"(d[O + 22]), "+f"(d[O + 23]), "+f"(d[O + 24]), "+f"(d[O + 25]), "+f"(d[O + 26]), "+f"(d[O + 27]), "+f"(d[O + 28]), "+f"(d[O + 29]), "+f"(d[O + 30]), "+f"(d[O + 31]), "+f"(d[O + 32]), "+f"(d[O + 33]), "+f"(d[O + 34]), "+f"(d[O + 35]), "+f"(d[O + 36]), "+f"(d[O + 37]), "+f"(d[O + 38]), "+f"(d[O + 39])
    : "r"(a0), "r"(a1), "r"(a2), "r"(a3), "l"(db));
  else asm volatile("{\n.reg .pred p;\nsetp.ne.b32 p, 0, 0;\n"
    "wgmma.mma_async.sync.aligned.m64n80k16.f32.bf16.bf16 {%0, %1, %2, %3, %4, %5, %6, %7, %8, %9, %10, %11, %12, %13, %14, %15, %16, %17, %18, %19, %20, %21, %22, %23, %24, %25, %26, %27, %28, %29, %30, %31, %32, %33, %34, %35, %36, %37, %38, %39}, {%40, %41, %42, %43}, %44, p, 1, 1, 1;\n}\n"
    : "=f"(d[O + 0]), "=f"(d[O + 1]), "=f"(d[O + 2]), "=f"(d[O + 3]), "=f"(d[O + 4]), "=f"(d[O + 5]), "=f"(d[O + 6]), "=f"(d[O + 7]), "=f"(d[O + 8]), "=f"(d[O + 9]), "=f"(d[O + 10]), "=f"(d[O + 11]), "=f"(d[O + 12]), "=f"(d[O + 13]), "=f"(d[O + 14]), "=f"(d[O + 15]), "=f"(d[O + 16]), "=f"(d[O + 17]), "=f"(d[O + 18]), "=f"(d[O + 19]), "=f"(d[O + 20]), "=f"(d[O + 21]), "=f"(d[O + 22]), "=f"(d[O + 23]), "=f"(d[O + 24]), "=f"(d[O + 25]), "=f"(d[O + 26]), "=f"(d[O + 27]), "=f"(d[O + 28]), "=f"(d[O + 29]), "=f"(d[O + 30]), "=f"(d[O + 31]), "=f"(d[O + 32]), "=f"(d[O + 33]), "=f"(d[O + 34]), "=f"(d[O + 35]), "=f"(d[O + 36]), "=f"(d[O + 37]), "=f"(d[O + 38]), "=f"(d[O + 39])
    : "r"(a0), "r"(a1), "r"(a2), "r"(a3), "l"(db));
  db += st;
}
template<int O, int SD, int L> __device__ __forceinline__ void rs88k(float (&d)[L], uint32_t a0, uint32_t a1, uint32_t a2, uint32_t a3, uint64_t& db, uint32_t st) {
  if (SD) asm volatile("{\n.reg .pred p;\nsetp.ne.b32 p, 1, 0;\n"
    "wgmma.mma_async.sync.aligned.m64n88k16.f32.bf16.bf16 {%0, %1, %2, %3, %4, %5, %6, %7, %8, %9, %10, %11, %12, %13, %14, %15, %16, %17, %18, %19, %20, %21, %22, %23, %24, %25, %26, %27, %28, %29, %30, %31, %32, %33, %34, %35, %36, %37, %38, %39, %40, %41, %42, %43}, {%44, %45, %46, %47}, %48, p, 1, 1, 0;\n}\n"
    : "+f"(d[O + 0]), "+f"(d[O + 1]), "+f"(d[O + 2]), "+f"(d[O + 3]), "+f"(d[O + 4]), "+f"(d[O + 5]), "+f"(d[O + 6]), "+f"(d[O + 7]), "+f"(d[O + 8]), "+f"(d[O + 9]), "+f"(d[O + 10]), "+f"(d[O + 11]), "+f"(d[O + 12]), "+f"(d[O + 13]), "+f"(d[O + 14]), "+f"(d[O + 15]), "+f"(d[O + 16]), "+f"(d[O + 17]), "+f"(d[O + 18]), "+f"(d[O + 19]), "+f"(d[O + 20]), "+f"(d[O + 21]), "+f"(d[O + 22]), "+f"(d[O + 23]), "+f"(d[O + 24]), "+f"(d[O + 25]), "+f"(d[O + 26]), "+f"(d[O + 27]), "+f"(d[O + 28]), "+f"(d[O + 29]), "+f"(d[O + 30]), "+f"(d[O + 31]), "+f"(d[O + 32]), "+f"(d[O + 33]), "+f"(d[O + 34]), "+f"(d[O + 35]), "+f"(d[O + 36]), "+f"(d[O + 37]), "+f"(d[O + 38]), "+f"(d[O + 39]), "+f"(d[O + 40]), "+f"(d[O + 41]), "+f"(d[O + 42]), "+f"(d[O + 43])
    : "r"(a0), "r"(a1), "r"(a2), "r"(a3), "l"(db));
  else asm volatile("{\n.reg .pred p;\nsetp.ne.b32 p, 0, 0;\n"
    "wgmma.mma_async.sync.aligned.m64n88k16.f32.bf16.bf16 {%0, %1, %2, %3, %4, %5, %6, %7, %8, %9, %10, %11, %12, %13, %14, %15, %16, %17, %18, %19, %20, %21, %22, %23, %24, %25, %26, %27, %28, %29, %30, %31, %32, %33, %34, %35, %36, %37, %38, %39, %40, %41, %42, %43}, {%44, %45, %46, %47}, %48, p, 1, 1, 0;\n}\n"
    : "=f"(d[O + 0]), "=f"(d[O + 1]), "=f"(d[O + 2]), "=f"(d[O + 3]), "=f"(d[O + 4]), "=f"(d[O + 5]), "=f"(d[O + 6]), "=f"(d[O + 7]), "=f"(d[O + 8]), "=f"(d[O + 9]), "=f"(d[O + 10]), "=f"(d[O + 11]), "=f"(d[O + 12]), "=f"(d[O + 13]), "=f"(d[O + 14]), "=f"(d[O + 15]), "=f"(d[O + 16]), "=f"(d[O + 17]), "=f"(d[O + 18]), "=f"(d[O + 19]), "=f"(d[O + 20]), "=f"(d[O + 21]), "=f"(d[O + 22]), "=f"(d[O + 23]), "=f"(d[O + 24]), "=f"(d[O + 25]), "=f"(d[O + 26]), "=f"(d[O + 27]), "=f"(d[O + 28]), "=f"(d[O + 29]), "=f"(d[O + 30]), "=f"(d[O + 31]), "=f"(d[O + 32]), "=f"(d[O + 33]), "=f"(d[O + 34]), "=f"(d[O + 35]), "=f"(d[O + 36]), "=f"(d[O + 37]), "=f"(d[O + 38]), "=f"(d[O + 39]), "=f"(d[O + 40]), "=f"(d[O + 41]), "=f"(d[O + 42]), "=f"(d[O + 43])
    : "r"(a0), "r"(a1), "r"(a2), "r"(a3), "l"(db));
  db += st;
}
template<int O, uint32_t HI, int SD, int L> __device__ __forceinline__ void ss48tt(float (&d)[L], uint32_t alo, uint32_t blo) {
  if (SD) asm volatile("{\n.reg .pred p;\n.reg .b64 da, db;\nsetp.ne.b32 p, 1, 0;\nmov.b64 da, {%24, %26};\nmov.b64 db, {%25, %26};\n"
    "wgmma.mma_async.sync.aligned.m64n48k16.f32.bf16.bf16 {%0, %1, %2, %3, %4, %5, %6, %7, %8, %9, %10, %11, %12, %13, %14, %15, %16, %17, %18, %19, %20, %21, %22, %23}, da, db, p, 1, 1, 1, 1;\n}\n"
    : "+f"(d[O + 0]), "+f"(d[O + 1]), "+f"(d[O + 2]), "+f"(d[O + 3]), "+f"(d[O + 4]), "+f"(d[O + 5]), "+f"(d[O + 6]), "+f"(d[O + 7]), "+f"(d[O + 8]), "+f"(d[O + 9]), "+f"(d[O + 10]), "+f"(d[O + 11]), "+f"(d[O + 12]), "+f"(d[O + 13]), "+f"(d[O + 14]), "+f"(d[O + 15]), "+f"(d[O + 16]), "+f"(d[O + 17]), "+f"(d[O + 18]), "+f"(d[O + 19]), "+f"(d[O + 20]), "+f"(d[O + 21]), "+f"(d[O + 22]), "+f"(d[O + 23])
    : "r"(alo), "r"(blo), "n"(HI));
  else asm volatile("{\n.reg .pred p;\n.reg .b64 da, db;\nsetp.ne.b32 p, 0, 0;\nmov.b64 da, {%24, %26};\nmov.b64 db, {%25, %26};\n"
    "wgmma.mma_async.sync.aligned.m64n48k16.f32.bf16.bf16 {%0, %1, %2, %3, %4, %5, %6, %7, %8, %9, %10, %11, %12, %13, %14, %15, %16, %17, %18, %19, %20, %21, %22, %23}, da, db, p, 1, 1, 1, 1;\n}\n"
    : "=f"(d[O + 0]), "=f"(d[O + 1]), "=f"(d[O + 2]), "=f"(d[O + 3]), "=f"(d[O + 4]), "=f"(d[O + 5]), "=f"(d[O + 6]), "=f"(d[O + 7]), "=f"(d[O + 8]), "=f"(d[O + 9]), "=f"(d[O + 10]), "=f"(d[O + 11]), "=f"(d[O + 12]), "=f"(d[O + 13]), "=f"(d[O + 14]), "=f"(d[O + 15]), "=f"(d[O + 16]), "=f"(d[O + 17]), "=f"(d[O + 18]), "=f"(d[O + 19]), "=f"(d[O + 20]), "=f"(d[O + 21]), "=f"(d[O + 22]), "=f"(d[O + 23])
    : "r"(alo), "r"(blo), "n"(HI));
}

constexpr uint32_t HI128 = 0x40000040u;
constexpr uint32_t HI64 = 0x80000020u;
constexpr uint32_t HI32 = 0xC0000010u;

__device__ __forceinline__ uint64_t desc(uint32_t lo, uint32_t hi) { return (uint64_t)hi << 32 | lo; }
__device__ __forceinline__ bool elect() {
  uint32_t p;
  asm volatile("{\n.reg .pred p;\nelect.sync _|p, 0xffffffff;\nselp.u32 %0, 1, 0, p;\n}" : "=r"(p));
  return p;
}
struct Ring {
  uint32_t fb, lo, ph;
  __device__ __forceinline__ void at(uint32_t it, uint32_t base) {
    const uint32_t rev = (it * 205u) >> 11, slot = it - rev * NSLOT;
    fb = base + OFF_BAR + 8 * slot; lo = (base >> 4) + slot * (SLOT / 16); ph = rev & 1;
  }
  template<int N> __device__ __forceinline__ void next(uint32_t bars) {
    asm("{\n.reg .pred p;\nadd.u32 %0, %0, %4;\nadd.u32 %1, %1, %5;\nsetp.ge.u32 p, %0, %3;\n"
        "@p sub.u32 %0, %0, %6;\n@p sub.u32 %1, %1, %7;\n@p xor.b32 %2, %2, 1;\n}"
        : "+r"(fb), "+r"(lo), "+r"(ph) : "r"(bars + 8 * NSLOT), "n"(8 * N), "n"(N * (SLOT / 16)), "n"(8 * NSLOT), "n"(NSLOT * (SLOT / 16)));
  }
};

template<int N>
__device__ __forceinline__ void tile_mma(float (&acc)[48], const uint32_t (&a)[160], int t, uint32_t base, bool lane0, uint32_t sig) {
  const uint32_t bars = base + OFF_BAR;
  uint32_t prev = 0;
  Ring r;
  r.at(8 * t + (t >= 2 ? 2 : 0), base);
  TWAIT(r.fb, r.ph, 96 + (sig - 3) * 16 + t);
  #pragma unroll
  for (int st = 0; st < 8; st++) {
    uint64_t db = desc(r.lo | (640u << 16), HI128), d2 = desc(r.lo + 640, HI128);
    const uint32_t cur = r.fb;
    wg_fence();
    #pragma unroll
    for (int kk = 0; kk < 5; kk++) {
      const int k = 4 * (st * 5 + kk);
      if (k == 0) {
        if (N == 80) rs80<0, 0>(acc, a[k], a[k + 1], a[k + 2], a[k + 3], db, 128);
        else if (N == 96) rs96<0, 0>(acc, a[k], a[k + 1], a[k + 2], a[k + 3], db, 128);
        else { rs48<0, 0>(acc, a[k], a[k + 1], a[k + 2], a[k + 3], db, 128); rs48<24, 0>(acc, a[k], a[k + 1], a[k + 2], a[k + 3], d2, 128); }
      } else {
        if (N == 80) rs80<0, 1>(acc, a[k], a[k + 1], a[k + 2], a[k + 3], db, 128);
        else if (N == 96) rs96<0, 1>(acc, a[k], a[k + 1], a[k + 2], a[k + 3], db, 128);
        else { rs48<0, 1>(acc, a[k], a[k + 1], a[k + 2], a[k + 3], db, 128); rs48<24, 1>(acc, a[k], a[k + 1], a[k + 2], a[k + 3], d2, 128); }
      }
    }
    wg_commit();
    if (st == S0 - 1) asm volatile("bar.arrive %0, 256;" :: "r"(sig) : "memory");
    r.next<1>(bars);
    if (st > 0) { wg_wait<1>(); if (lane0) mbar_arrive(prev + 80); }
    if (st < 7) TWAIT(r.fb, r.ph, 96 + (sig - 3) * 16 + t);
    prev = cur;
  }
  wg_wait<0>();
  if (lane0) mbar_arrive(prev + 80);
  pin<0, N == 80 ? 40 : 48>(acc);
}

struct Maps { CUtensorMap x, qkv64, qkv16, w1a, w1b, w3a, w3b, w1c, w3c, w2a, w2b, woa, wob, xa, xb; };

__global__ void __launch_bounds__(384, 1)
fused_kernel(const __grid_constant__ Maps M, char* __restrict__ out) {
  extern __shared__ __align__(1024) uint8_t smem_raw[];
  asm volatile("prefetch.tensormap [%0];" :: "l"(&M.x) : "memory");
  const uint32_t base = (smem_u32(smem_raw) + 1023) & ~1023u;
  const uint32_t bars = base + OFF_BAR;
  const int tid = threadIdx.x;
  const int warp = __shfl_sync(0xffffffffu, tid >> 5, 0);
  const int b = blockIdx.x;
  const int rb = ((b >> 4) & 3) * 4 + (b & 1) + ((b >> 2) & 2), role = b >> 6, p = (b >> 1) & 3, mate = b ^ 64;
  if ((warp >> 1) == 4 && elect()) {
    const int w = warp & 1;
    if (!w) PROFT_(0);
    uint32_t xb = bars + 8 * (B_XFULL + 5 * w), xd = base + (3 + 4 * w) * SLOT;
    #pragma unroll
    for (int i = 0; i < 5; i++) mbar_init(xb + 8 * i, 1);
    asm volatile("fence.proxy.async.shared::cta;" ::: "memory");
    #pragma unroll 1
    for (int i = -DLY * w; i < 10; i += 2) {
      if (i < 0) continue;
      mbar_expect(xb, 16384);
      tma3d(xd, &M.x, 0, rb * 128 + 64 * w, i, xb);
      xb += 8; xd += 16384 + (i ? 0 : 4096 * w);
    }
  }
  const int g = 2 * p + role;
  const int nt = role ? 7 : 8;
  const int cl = 160 * p + (p & 1) * 32 + 64 * role, ch = 160 * p + (~p & 1) * 128;

  if (warp < 8) goto CONSUMER;
  asm volatile("setmaxnreg.dec.sync.aligned.u32 24;");
  if (warp >= 10) goto PUBLISHER;
  asm volatile("bar.sync 0, 384;" ::: "memory");
  {
      if (elect()) {
        const int w = warp - 8;
        mbar_wait(bars + 8 * B_XFULL, 0);
        Ring r{bars + 8 * w, (base + w * SLOT) >> 4, 1};
        uint32_t fb, dst;
        auto acquire = [&](uint32_t bytes) {
          mbar_wait(r.fb + 80, r.ph);
          fb = r.fb; dst = r.lo << 4;
          mbar_expect(fb, bytes);
          r.next<2>(bars);
        };
        #pragma unroll 1
        for (int t = 0; t < nt; t++) {
          const CUtensorMap* m0 = &M.qkv64; const CUtensorMap* m1 = &M.qkv16;
          int c0, c1; uint32_t bytes = 15360;
          if (t < 2 || t == nt - 1) { c0 = (t < 2 ? 640 + 640 * t : 0) + 80 * g; c1 = c0 + 64; bytes = 12800; }
          else if (t == 6) { c0 = c1 = 1536 + 48 * p; m0 = &M.w1c; m1 = &M.w3c; }
          else {
            c0 = c1 = 96 * (4 * (t - 2 & ~1) + g);
            if (t & 1) { m0 = &M.w3a; m1 = &M.w1b; c0 += 32; c1 += 64; } else { m0 = &M.w1a; m1 = &M.w3b; }
          }
          #pragma unroll 1
          for (int st = w; st < 8; st += 2) {
            const int it = 8 * t + st;
            if (it >= 3 && it < 10) mbar_wait(bars + 8 * (B_XFREE + (it < 7 ? 0 : it == 7 ? 2 : 1)), 0);
            acquire(bytes);
            tma2d(dst, m0, c0, 80 * st, fb);
            tma2d(dst + 10240, m1, c1, 80 * st, fb);
          }
          if (t == 1) acquire(0);
        }
        PROFT(40 + 8 * w);
        const int k0 = role ? 0 : NY, k1 = role ? NY : 108;
        if (w == 0) {
          int j6 = 0; uint32_t pa = 0;
          auto acquire6 = [&](uint32_t bytes) {
            if (j6 == 5) {
              fb = bars + 8 * B_AUXF; dst = base + OFF_AUX;
              mbar_wait(fb + 80, pa);
              mbar_expect(fb, bytes);
              j6 = 0; pa ^= 1;
            } else { acquire(bytes); j6++; }
          };
          #pragma unroll 1
          for (int k = k0; k < k1; k += k == k0 ? 2 : 4) {
            acquire6(20480);
            tma2d(dst, &M.w2a, cl, 16 * k, fb);
            tma2d(dst + 8192, &M.w2a, cl + 64 - 128 * role, 16 * k, fb);
            tma2d(dst + 16384, &M.w2b, ch, 16 * k, fb);
            PROFT(188 + (k - k0 + 2) / 4);
          }
          #pragma unroll 1
          for (int m = 0; m < 8; m++) {
            const int gm = m < 4 ? 2 * m + 1 : 2 * m - 8;
            acquire6(12800);
            tma2d(dst, &M.woa, cl, 80 * gm, fb);
            tma2d(dst + 10240, &M.wob, ch + 16 * role, 80 * gm, fb);
            PROFT(208 + m);
          }
        } else {
          auto ready = [&](int i) { mbar_wait(bars + 8 * (B_OK + i), 0); asm volatile("fence.proxy.async.global;" ::: "memory"); };
          #pragma unroll 1
          for (int k = k0, n = 2; k < k1; k += n, n = 4) {
            if (k == k0 || k == (role ? 46 : 96)) ready(k != k0);
            acquire(n * 4096);
            bulk(dst, g_h + (rb * 108 + k) * 256, n * 4096, fb);
            PROFT(168 + (k - k0 + 2) / 4);
          }
          PROFT(49);
          #pragma unroll 1
          for (int m = 0; m < 8; m++) {
            if (!(m & 3)) ready(2 + (m >> 2));
            acquire(20480);
            bulk(dst, g_o + (rb * 40 + 5 * (m < 4 ? 2 * m + 1 : 2 * m - 8)) * 256, 20480, fb);
            PROFT(216 + m);
          }
          acquire(20480);
          tma2d(dst, &M.xa, cl, rb * 128, fb);
          tma2d(dst + 16384, &M.xb, ch + 16 * role, rb * 128, fb);
        }
      }
    PROFEND();
    return;
  }
CONSUMER:
  {
    asm volatile("setmaxnreg.inc.sync.aligned.u32 240;");
    const int wg = warp >> 2, w4 = warp & 3, lane = tid & 31;
    const bool lane0 = lane == 0;
    uint32_t a[160];
    float r0, r1;
    asm volatile("bar.sync 0, 384;" ::: "memory");
    {
      const int row = w4 * 16 + (lane & 15);
      const uint32_t xa = base + (wg ? 7 : 3) * SLOT + row * 128, xb = xa + wg * 4096;
      float st[2][4], sq[4][4];
      #pragma unroll
      for (int i = 0; i < 8; i++) st[i >> 2][i & 3] = 0.f;
      #pragma unroll
      for (int i = 0; i < 16; i++) sq[i >> 2][i & 3] = 0.f;
      #pragma unroll
      for (int i = 0; i < 10; i++) {
        if (i == 0) PROFC(32 + wg * 4);
        if (!(i & 1)) mbar_wait(bars + 8 * (B_XFULL + wg * 5 + (i >> 1)), 0);
        if (i == 0) PROFC(33 + wg * 4);
        if (i == 8) PROFC(34 + wg * 4);
        #pragma unroll
        for (int j = 0; j < 4; j++) {
          const int k = 16 * i + 4 * j;
          asm volatile("ldmatrix.sync.aligned.m8n8.x4.shared.b16 {%0,%1,%2,%3}, [%4];" : "=r"(a[k]), "=r"(a[k + 1]), "=r"(a[k + 2]), "=r"(a[k + 3])
                       : "r"((i < 2 ? xa : xb) + i * 8192 + (((2 * j + (lane >> 4)) ^ (row & 7)) << 4)) : "memory");
        }
        if (i == 1 && lane0 && wg) mbar_arrive(bars + 8 * (B_XFREE + 2) + (a[31] & blockIdx.y));
        #pragma unroll
        for (int j = 0; j < 4; j++) { const int k = 16 * i + 4 * j; mma16(st[j & 1], a[k], a[k + 1], a[k + 2], a[k + 3], 0x3f803f80u, 0x3f803f80u); }
        if ((i & 1) && !wg) {
          #pragma unroll
          for (int j = 0; j < 8; j++) {
            const int k = 16 * i - 16 + 4 * j;
            mma16(sq[j & 1], a[k], a[k + 1], a[k + 2], a[k + 3], a[k], a[k + 2]);
            mma16(sq[2 + (j & 1)], a[k], a[k + 1], a[k + 2], a[k + 3], a[k + 1], a[k + 3]);
          }
        }
      }
      const float m0 = (st[0][0] + st[1][0]) * (1.f / 640), m1 = (st[0][2] + st[1][2]) * (1.f / 640);
      if (lane0) mbar_arrive(bars + 8 * (B_XFREE + wg) + (__float_as_uint(m0) & blockIdx.y));
      PROFC(35 + wg * 4);
      uint32_t b0 = pack(m0, m0), b1 = pack(m1, m1);
      uint32_t dep = 0;
      asm volatile("{\n.reg .pred p;\nsetp.ne.u32 p, %1, 0;\n@p bar.sync 6, 256;\n@p ld.shared.u32 %0, [%2];\n}" : "+r"(dep) : "r"(wg), "r"(base + OFF_EP) : "memory");
      b0 ^= dep & blockIdx.y; b1 ^= dep & blockIdx.y;
      #pragma unroll
      for (int k = 0; k < 160; k++) asm("sub.rn.bf16x2 %0, %0, %1;" : "+r"(a[k]) : "r"((k & 1) ? b1 : b0));
      const bool dg = (lane & 3) == (lane >> 3);
      r0 = fmaf(-0.25f * m0, m0, dg ? ((lane & 4) ? sq[0][1] + sq[1][1] : sq[0][0] + sq[1][0]) * (1.f / 640) : 0.f);
      r1 = fmaf(-0.25f * m1, m1, dg ? ((lane & 4) ? sq[2][3] + sq[3][3] : sq[2][2] + sq[3][2]) * (1.f / 640) : 0.f);
      if (wg) {
        float q0 = 0.f, q1 = 0.f;
        #pragma unroll
        for (int k = 0; k < 160; k += 20) {
          uint32_t u0 = hmul(a[k], a[k]), u1 = hmul(a[k + 1], a[k + 1]);
          #pragma unroll
          for (int j = 2; j < 20; j += 2) { u0 = hfma(a[k + j], a[k + j], u0); u1 = hfma(a[k + j + 1], a[k + j + 1], u1); }
          q0 += blo(u0) + bhi(u0); q1 += blo(u1) + bhi(u1);
        }
        const float e0 = m0 - blo(b0), e1 = m1 - blo(b1);
        r0 = fmaf(-0.25f * e0, e0, q0 * (1.f / 640));
        r1 = fmaf(-0.25f * e1, e1, q1 * (1.f / 640));
      }
    }
    asm volatile("{\n.reg .pred p;\nsetp.eq.u32 p, %0, 0;\n@p bar.arrive 6, 256;\n}" :: "r"(wg + (a[159] & blockIdx.y)) : "memory");
    PROFL(1 + wg * 16);
    float acc[48];
    const uint32_t evb = bars + 8 * (B_EV + wg * 5);
    #pragma unroll 1
    for (int tv = 0;; tv++) {
      const int t = __shfl_sync(0xffffffffu, tv, 0);
      PROFL(64 + wg * 16 + t);
      if (wg || t) asm volatile("bar.sync %0, 256;" :: "r"(4 - wg) : "memory");
      if (t < 2 || t == nt - 1) {
        tile_mma<80>(acc, a, t, base, lane0, 3 + wg);
        if (t >= 2) break;
        PROFL(2 + t + wg * 16);
        asm volatile("" : "+f"(r0), "+f"(r1));
        const int lane = fresh_tid() & 31, t4 = lane & 3;
        const int row = w4 * 16 + (lane & 15);
        const uint32_t so = row * 32 + ((((lane >> 4) ^ (row >> 2)) & 1) << 4);
        const uint32_t PK = base + OFF_AUX + wg * 10240;
        if (t == 0) {
          r0 += __shfl_xor_sync(0xffffffffu, r0, 1); r1 += __shfl_xor_sync(0xffffffffu, r1, 1);
          r0 += __shfl_xor_sync(0xffffffffu, r0, 2); r1 += __shfl_xor_sync(0xffffffffu, r1, 2);
          r0 = rsqrtf(fmaxf(r0, 0.f) + 1e-5f); r1 = rsqrtf(fmaxf(r1, 0.f) + 1e-5f);
          const float k0 = r0 * LOG2E, k1 = r1 * LOG2E;
          mbar_wait(bars + 8 * (B_XFREE + 1), 0);
          #pragma unroll
          for (int i = 0; i < 5; i++)
            stsm4(PK + so + i * 2048, phi2<1>(acc[8 * i], acc[8 * i + 1], r0, k0), phi2<1>(acc[8 * i + 2], acc[8 * i + 3], r1, k1),
                  phi2<1>(acc[8 * i + 4], acc[8 * i + 5], r0, k0), phi2<1>(acc[8 * i + 6], acc[8 * i + 7], r1, k1));
          continue;
        }
        mbar_wait(bars + 8 * (6 + wg), 1);
        const uint32_t VS = base + (6 + wg) * SLOT;
        {
          uint32_t v[20];
          #pragma unroll
          for (int i = 0; i < 20; i++) v[i] = pack(acc[2 * i], acc[2 * i + 1]);
          const float s0 = rcp(r0), s1 = rcp(r1);
          const uint32_t o0 = t4 == 0 ? pack(s0, s0 - blo(pack(s0, 0.f))) : 0u, o1 = t4 == 0 ? pack(s1, s1 - blo(pack(s1, 0.f))) : 0u;
          stsm4(VS + so, v[0], v[1], v[2], v[3]); stsm4(VS + so + 2048, v[4], v[5], v[6], v[7]); stsm4(VS + so + 4096, v[8], v[9], o0, o1);
          stsm4(VS + so + 6144, v[10], v[11], v[12], v[13]); stsm4(VS + so + 8192, v[14], v[15], v[16], v[17]); stsm4(VS + so + 10240, v[18], v[19], o0, o1);
        }
        PROFC(54 + wg * 5);
        asm volatile("fence.proxy.async.shared::cta;" ::: "memory");
        PROFC(55 + wg * 5);
        asm volatile("bar.sync %0, 128;" :: "r"(1 + wg) : "memory");
        PROFC(56 + wg * 5);
        const uint32_t al = (PK >> 4) | (128u << 16), bl = (VS >> 4) | (128u << 16);
        wg_fence();
        ss48tt<0, HI32, 0>(acc, al, bl); ss48tt<24, HI32, 0>(acc, al + 256, bl + 384);
        #pragma unroll
        for (int kk = 1; kk < 4; kk++) { ss48tt<0, HI32, 1>(acc, al + 32 * kk, bl + 32 * kk); ss48tt<24, HI32, 1>(acc, al + 256 + 32 * kk, bl + 384 + 32 * kk); }
        wg_commit();
        const int m0 = w4 * 16 + (lane >> 2);
        const uint32_t dst = VS + 12288 + m0 * 96 + t4 * 8;
        wg_wait<0>();
        pin<0, 48>(acc);
        PROFC(57 + wg * 5);
        #pragma unroll
        for (int i = 0; i < 4; i++) {
          const int j = i >> 1, hf = i & 1;
          const uint32_t d = m0 + 8 * hf - 8 * j;
          const uint32_t dr = dst + (j * 40 + 8 * hf - 8 * j) * 96;
          const float* c = &acc[24 * j + 2 * hf];
          asm volatile("{\n.reg .pred v, h, l, t, m, z;\n.reg .u32 b;\n"
                       "setp.lt.u32 l, %0, 20;\nsetp.lt.u32 v, %0, 40;\nsetp.lt.u32 t, %1, 2;\n"
                       "xor.pred h, v, l;\nand.pred z, v, t;\nxor.pred m, h, z;\n"
                       "selp.u32 b, 80, 0, h;\nsub.u32 b, %2, b;\n"
                       "@l st.shared.v2.f32 [%2], {%3, %4};\n@l st.shared.v2.f32 [%2 + 32], {%5, %6};\n@m st.shared.v2.f32 [b + 64], {%7, %8};\n"
                       "@h st.shared.v2.f32 [%2 + 16], {%9, %10};\n@h st.shared.v2.f32 [%2 + 48], {%11, %12};\n@z st.shared.v2.f32 [%2 + 80], {%13, %14};\n}"
                       :: "r"(d), "r"(t4), "r"(dr), "f"(c[0]), "f"(c[1]), "f"(c[4]), "f"(c[5]), "f"(c[8]), "f"(c[9]),
                          "f"(c[12]), "f"(c[13]), "f"(c[16]), "f"(c[17]), "f"(c[20]), "f"(c[21]) : "memory");
        }
        PROFC(58 + wg * 5);
        asm volatile("fence.proxy.async.shared::cta;" ::: "memory");
        __syncwarp();
        if (lane0) mbar_arrive(evb);
        PROFC(15 + wg * 16);
        continue;
      }
      if (t == 6) {
        tile_mma<48>(acc, a, t, base, lane0, 3 + wg);
        PROFL(2 + t + wg * 16);
        asm volatile("" : "+f"(r0), "+f"(r1));
        const float k0 = 0.5f * r0, k1 = 0.5f * r1;
        uint4* dst = g_h + (rb * 108 + 96 + 3 * p) * 256 + fresh_tid();
        #pragma unroll
        for (int s = 0; s < 3; s++) {
          uint32_t h[4];
          #pragma unroll
          for (int c = 0; c < 4; c++) {
            const int o = 8 * s + 2 * c; const float rr = (c & 1) ? r1 : r0, kk = (c & 1) ? k1 : k0;
            h[c] = pack(silu2(acc[o] * kk) * (acc[24 + o] * rr), silu2(acc[o + 1] * kk) * (acc[25 + o] * rr));
          }
          dst[s * 256] = make_uint4(h[0], h[1], h[2], h[3]);
        }
        __syncwarp();
        if (lane0) mbar_arrive(evb + 8 * 3);
        continue;
      }
      tile_mma<96>(acc, a, t, base, lane0, 3 + wg);
      PROFL(2 + t + wg * 16);
      asm volatile("" : "+f"(r0), "+f"(r1));
      const int tid = fresh_tid();
      const float k0 = 0.5f * r0, k1 = 0.5f * r1;
      const uint32_t stash = base + OFF_AUX + 20480 - wg * 4096 + (tid & 127) * 16;
      uint4* dst = g_h + (rb * 108 + 6 * (4 * (t - 2 & ~1) + g)) * 256 + tid;
      if (!(t & 1)) {
        #pragma unroll
        for (int s = 0; s < 4; s++) {
          uint32_t h[4];
          #pragma unroll
          for (int c = 0; c < 4; c++) {
            const int o = 8 * s + 2 * c; const float rr = (c & 1) ? r1 : r0, kk = (c & 1) ? k1 : k0;
            h[c] = s < 2 ? pack(silu2(acc[o] * kk) * (acc[32 + o] * rr), silu2(acc[o + 1] * kk) * (acc[33 + o] * rr)) : pack(silu2(acc[o] * kk), silu2(acc[o + 1] * kk));
          }
          if (s < 2) dst[s * 256] = make_uint4(h[0], h[1], h[2], h[3]); else sts128(stash + (s - 2) * 2048, h[0], h[1], h[2], h[3]);
        }
        continue;
      }
      #pragma unroll
      for (int s = 0; s < 4; s++) {
        uint32_t h[4];
        if (s < 2) {
          const uint4 u = lds128(stash + s * 2048);
          h[0] = pack(blo(u.x) * (acc[8 * s] * r0), bhi(u.x) * (acc[8 * s + 1] * r0)); h[1] = pack(blo(u.y) * (acc[8 * s + 2] * r1), bhi(u.y) * (acc[8 * s + 3] * r1));
          h[2] = pack(blo(u.z) * (acc[8 * s + 4] * r0), bhi(u.z) * (acc[8 * s + 5] * r0)); h[3] = pack(blo(u.w) * (acc[8 * s + 6] * r1), bhi(u.w) * (acc[8 * s + 7] * r1));
        } else {
          #pragma unroll
          for (int c = 0; c < 4; c++) {
            const int o = 8 * s + 2 * c; const float rr = (c & 1) ? r1 : r0, kk = (c & 1) ? k1 : k0;
            h[c] = pack(silu2(acc[16 + o] * kk) * (acc[o] * rr), silu2(acc[17 + o] * kk) * (acc[o + 1] * rr));
          }
        }
        dst[(2 + s) * 256] = make_uint4(h[0], h[1], h[2], h[3]);
      }
      __syncwarp();
      if (lane0) mbar_arrive(evb + 8 * (t >> 1));
    }
    float c1[64], c2[16];
    uint4 fa[3][5];
    Ring r;
    r.at(8 * nt + 2, base);
    {
      PROFL(9 + wg * 16);
      const int t4 = lane & 3;
      const float k0 = r0 * LOG2E, k1 = r1 * LOG2E;
      uint32_t q[20];
      #pragma unroll
      for (int i = 0; i < 20; i++) q[i] = phi2<0>(acc[2 * i], acc[2 * i + 1], (i & 1) ? r1 : r0, (i & 1) ? k1 : k0);
      PROFC(41 + wg * 3);
      mbar_wait(bars + 8 * B_KVRDY, 0);
      uint64_t db = desc(((base + OFF_AUX) >> 4) | (1u << 16), HI32);
      wg_fence();
      rs88k<0, 0>(acc, q[0], q[1], q[2], q[3], db, 176);
      #pragma unroll
      for (int s = 1; s < 5; s++) rs88k<0, 1>(acc, q[4 * s], q[4 * s + 1], q[4 * s + 2], q[4 * s + 3], db, 176);
      wg_commit();
      mbar_wait(r.fb + 8, r.ph);
      #pragma unroll
      for (int kk = 0; kk < 2; kk++) fa[0][kk] = lds128((r.lo << 4) + SLOT + kk * 4096 + tid * 16);
      #pragma unroll
      for (int i = 0; i < 64; i++) c1[i] = 0.f;
      #pragma unroll
      for (int i = 0; i < 16; i++) c2[i] = 0.f;
      pin<0, 64>(c1); pin<0, 16>(c2);
      mbar_wait(r.fb, r.ph);
      if (!wg) asm volatile("bar.sync 4, 256;" ::: "memory");
      PROFC(42 + wg * 3);
      wg_wait<0>();
      pin<0, 44>(acc);
      if (lane0) mbar_arrive(bars + 8 * (B_AUXF + 10));
      PROFC(43 + wg * 3);
      float dn[2][4];
      #pragma unroll
      for (int hf = 0; hf < 2; hf++) {
        const float u = rcp(acc[40 + 2 * hf] + 1e-6f), v = rcp(acc[41 + 2 * hf] + 1e-6f);
        dn[hf][0] = __shfl_sync(0xffffffffu, u, lane & 28); dn[hf][1] = __shfl_sync(0xffffffffu, v, lane & 28);
        dn[hf][2] = __shfl_sync(0xffffffffu, u, (lane & 28) + 1); dn[hf][3] = __shfl_sync(0xffffffffu, v, (lane & 28) + 1);
      }
      uint4* dst = g_o + (rb * 40 + 5 * g) * 256 + tid;
      #pragma unroll
      for (int s = 0; s < 5; s++) {
        uint32_t o[4];
        #pragma unroll
        for (int c = 0; c < 4; c++) {
          const int blk = 2 * s + (c >> 1), hf = c & 1;
          const float sc = blk == 2 ? (t4 < 2 ? dn[hf][0] : dn[hf][1]) : blk == 7 ? (t4 < 2 ? dn[hf][2] : dn[hf][3]) : dn[hf][(8 * blk) / 20];
          o[c] = pack(acc[4 * blk + 2 * hf] * sc, acc[4 * blk + 2 * hf + 1] * sc);
        }
        dst[s * 256] = make_uint4(o[0], o[1], o[2], o[3]);
      }
      __syncwarp();
      if (lane0) mbar_arrive(evb + 8 * (nt - 4));
      PROFL(10 + wg * 16);
    }
    {
      float c[40];
      uint4 xv[5], pv[5];
      uint32_t kp[20];
      uint32_t prev = 0;
      int sidx = 0;
      Ring wb = r, wn = r;
      wn.next<2>(bars);
      uint32_t pa = 0, xa = 0, xb = 0;
      const int row = warp * 16 + (lane & 15);
      const uint32_t xs = ((lane >> 4) ^ row) & 7;
      auto stage = [&](uint4 (&f)[5], int nk, uint4 (&fn)[5], int nn, bool fetch, bool rela, bool relb, bool toaux, auto issue, auto extra) {
        Ring n = r; n.next<2>(bars);
        if (lane0 && rela) mbar_arrive(r.fb + 88 + (f[nk - 1].w & blockIdx.y));
        TWAIT(n.fb + 8, n.ph, 104 + wg * 16 + (sidx ? 2 : 0));
        if (fetch) {
          #pragma unroll
          for (int kk = 0; kk < 5; kk++) if (kk < nn) fn[kk] = lds128((n.lo << 4) + SLOT + kk * 4096 + tid * 16);
        } else {
          xa = (n.lo << 4) + SLOT + row * 128;
          xb = (n.lo << 4) + SLOT + 16384 + row * 32 + ((((lane >> 4) ^ (row >> 2)) & 1) << 4);
          #pragma unroll
          for (int i = 0; i < 5; i++)
            asm volatile("ldmatrix.sync.aligned.m8n8.x4.shared.b16 {%0,%1,%2,%3}, [%4];" : "=r"(xv[i].x), "=r"(xv[i].y), "=r"(xv[i].z), "=r"(xv[i].w)
                         : "r"(i < 4 ? xa + ((xs ^ (2 * i)) << 4) : xb) : "memory");
        }
        wg_fence();
        issue(wb.lo);
        wg_commit();
        const uint32_t cur = wb.fb;
        if (toaux) { wb = Ring{bars + 8 * B_AUXF, (base + OFF_AUX) >> 4, pa}; pa ^= 1; } else { wb = wn; wn.next<2>(bars); }
        if (fetch) TWAIT(wb.fb, wb.ph, 105 + wg * 16 + (sidx ? 2 : 0));
        extra();
        wg_wait<1>();
        if (lane0 && relb) mbar_arrive(prev + 80);
        prev = cur;
        r = n;
      };
      auto down = [&](uint4 (&f)[5], int nk, uint4 (&fn)[5], int nn, bool relb, bool toaux) {
        stage(f, nk, fn, nn, true, true, relb, toaux, [&](uint32_t lo) {
          uint64_t d1 = desc(lo | (512u << 16), HI128), d2 = desc(lo + 1024, HI64);
          #pragma unroll
          for (int kk = 0; kk < 4; kk++) if (kk < nk) {
            rs128<0, 1>(c1, f[kk].x, f[kk].y, f[kk].z, f[kk].w, d1, 128);
            rs32<0, 1>(c2, f[kk].x, f[kk].y, f[kk].z, f[kk].w, d2, 64);
          }
        }, [] {});
      };
      auto outp = [&](uint4 (&f)[5], uint4 (&fn)[5], int k, auto extra) {
        const bool first = k == 0;
        PROFL(224 + wg * 10 + sidx); sidx++;
        stage(f, 5, fn, 5, k < 7, k < 4, k < 3, k == 5, [&](uint32_t lo) {
          uint64_t db = desc(lo | (640u << 16), HI128);
          if (first) rs80<0, 0>(c, f[0].x, f[0].y, f[0].z, f[0].w, db, 128); else rs80<0, 1>(c, f[0].x, f[0].y, f[0].z, f[0].w, db, 128);
          #pragma unroll
          for (int kk = 1; kk < 5; kk++) rs80<0, 1>(c, f[kk].x, f[kk].y, f[kk].z, f[kk].w, db, 128);
        }, extra);
      };
      const int ntrip = role ? 5 : 3;
      PROFL(127 - wg);
      down(fa[0], 2, fa[1], 4, false, false);
      #pragma unroll 1
      for (int m = 0;; m++) {
        PROFL(128 + wg * 20 + 3 * m);
        down(fa[1], 4, fa[2], 5, true, m & 1);
        if (m == ntrip) break;
        PROFC(129 + wg * 20 + 3 * m);
        down(fa[2], 4, fa[0], 4, true, false);
        PROFC(130 + wg * 20 + 3 * m);
        down(fa[0], 4, fa[1], 4, true, false);
      }
      uint32_t tag;
      asm volatile("ld.shared.u32 %0, [%1];" : "=r"(tag) : "r"(base + OFF_EP) : "memory");
      tag = (tag + 1) & 1;
      outp(fa[2], fa[0], 0, [] {});
      pin<0, 64>(c1); pin<0, 16>(c2);
      PROFC(11 + wg * 16);
      outp(fa[0], fa[1], 1, [&] {
        uint4* dst = g_p + (b * 8 + warp) * 160 + lane;
        auto put = [&](int i, const float* v) { stg_relaxed(dst + i * 32, (pack(v[0], v[1]) & ~1u) | tag, pack(v[2], v[3]), pack(v[4], v[5]), pack(v[6], v[7])); };
        #pragma unroll
        for (int i = 0; i < 4; i++) put(i, &c1[32 + 8 * i]);
        #pragma unroll
        for (int i = 0; i < 8; i++) { const float u = c2[i], v = c2[8 + i]; c2[i] = role ? v : u; c2[8 + i] = role ? u : v; }
        put(4, &c2[8]);
      });
      outp(fa[1], fa[2], 2, [] {});
      outp(fa[2], fa[0], 3, [&] {
        #pragma unroll
        for (int i = 0; i < 20; i++) { kp[i] = i < 16 ? pack(c1[2 * i], c1[2 * i + 1]) : pack(c2[2 * i - 32], c2[2 * i - 31]); asm volatile("" : "+r"(kp[i])); }
      });
      const uint4* src = g_p + (mate * 8 + warp) * 160 + lane;
      auto recv = [&] {
        #pragma unroll
        for (int i = 0; i < 5; i++) pv[i] = ldg_relaxed(src + i * 32);
      };
      auto check = [&] {
        uint32_t bad = 0, n = 0;
        #pragma unroll 1
        do {
          #pragma unroll
          for (int i = 0; i < 5; i++)
            asm volatile("{\n.reg .pred p;\nsetp.ne.u32 p, %5, 0;\n@p ld.relaxed.gpu.global.v4.u32 {%0, %1, %2, %3}, [%4];\n}"
                         : "+r"(pv[i].x), "+r"(pv[i].y), "+r"(pv[i].z), "+r"(pv[i].w) : "l"(src + i * 32), "r"(bad) : "memory");
          bad = 0;
          #pragma unroll
          for (int i = 0; i < 5; i++) bad |= pv[i].x ^ tag;
          bad = __any_sync(0xffffffffu, bad & 1);
        } while (bad && ++n < (1u << 18));
        PROFL(12 + wg * 16);
      };
      auto gate = [&](int i0, int i1) {
        #pragma unroll
        for (int i = i0; i < i1; i++) {
          const uint4 v = pv[i / 4]; const int j = i & 3;
          const uint32_t h = hmul(hadd(kp[i], j == 0 ? v.x : j == 1 ? v.y : j == 2 ? v.z : v.w), 0x3f003f00u);
          uint32_t t;
          asm("tanh.approx.bf16x2 %0, %1;" : "=r"(t) : "r"(h));
          kp[i] = hfma(h, t, h);
          asm volatile("" : "+r"(kp[i]));
        }
      };
      outp(fa[0], fa[1], 4, [] {});
      outp(fa[1], fa[2], 5, recv);
      outp(fa[2], fa[0], 6, [] {});
      outp(fa[0], fa[1], 7, [&] { check(); gate(0, 20); mbar_wait(bars + 8 * B_KVRDY, 0); });
      wg_wait<0>();
      pin<0, 40>(c);
      PROFL(13 + wg * 16);
      #pragma unroll
      for (int i = 0; i < 5; i++) {
        stsm4(i < 4 ? xa + ((xs ^ (2 * i)) << 4) : xb, hfma(pack(c[8 * i], c[8 * i + 1]), kp[4 * i], xv[i].x), hfma(pack(c[8 * i + 2], c[8 * i + 3]), kp[4 * i + 1], xv[i].y),
              hfma(pack(c[8 * i + 4], c[8 * i + 5]), kp[4 * i + 2], xv[i].z), hfma(pack(c[8 * i + 6], c[8 * i + 7]), kp[4 * i + 3], xv[i].w));
      }
      __syncwarp();
      {
        const int rw = warp * 16 + (lane >> 3), r2 = warp * 16 + (lane >> 1);
        const uint32_t xo = (r.lo << 4) + SLOT, la = xo + rw * 128 + (((lane ^ rw) & 7) << 4);
        char* oa = out + (uint32_t)((rb * 128 + rw) * 1280 + cl * 2 + (lane & 7) * 16);
        #pragma unroll
        for (int i = 0; i < 4; i++) *reinterpret_cast<uint4*>(oa + i * 5120) = lds128((la ^ ((i & 1) << 6)) + i * 512);
        *reinterpret_cast<uint4*>(out + (uint32_t)((rb * 128 + r2) * 1280 + (ch + 16 * role) * 2 + (lane & 1) * 16)) =
            lds128(xo + 16384 + r2 * 32 + (((lane ^ (r2 >> 2)) & 1) << 4));
      }
      PROFL(14 + wg * 16);
    }
    PROFEND();
    if (blockIdx.y == 0) return;
  }
PUBLISHER:
  {
    const int lane = tid & 31;
    if (elect()) {
      if (warp == 10) {
        #pragma unroll
        for (int i = 30; i < 51; i++) mbar_init(bars + 8 * i, i < 43 ? 4 : i == B_KVRDY ? 2 : 1);
        mbar_init(bars + 8 * (B_AUXF + 10), 8);
      } else {
        #pragma unroll
        for (int i = 0; i < 20; i++) mbar_init(bars + 8 * i, i < 10 ? 1 : 8);
      }
      asm volatile("fence.proxy.async.shared::cta;" ::: "memory");
    }
    asm volatile("bar.sync 0, 384;" ::: "memory");
    if (elect()) {
      #pragma unroll 1
      for (int i = warp - 9; i < 15; i += 2) asm volatile("prefetch.tensormap [%0];" :: "l"(&M.x + i) : "memory");
    }
      const int w = warp - 10, nev = role ? 4 : 5;
      unsigned ep = 0;
      if (lane == 0) {
        if (w) {
          ep = *(volatile unsigned*)&g_epoch[b];
          *(volatile unsigned*)&g_epoch[b] = ep + 1;
          asm volatile("st.shared.u32 [%0], %1;" :: "r"(base + OFF_EP), "r"(ep) : "memory");
          mbar_arrive(bars + 8 * B_EP);
        } else {
          mbar_wait(bars + 8 * B_EP, 0);
          asm volatile("ld.shared.u32 %0, [%1];" : "=r"(ep) : "r"(base + OFF_EP) : "memory");
        }
      }
      ep = __shfl_sync(0xffffffffu, ep, 0);
      if (w && lane < 30) reinterpret_cast<float4*>(g_kv + ((ep + 1) & 1) * 15360 + b * 120)[lane] = make_float4(0.f, 0.f, 0.f, 0.f);
      const float* kvs = g_kv + ((ep & 1) * 8 + g) * 1920;
      if (elect()) {
        mbar_wait(bars + 8 * (B_EV + w * 5), 0);
        asm volatile("cp.reduce.async.bulk.global.shared::cta.bulk_group.add.f32 [%0], [%1], 7680;" :: "l"(kvs), "r"(base + (6 + w) * SLOT + 12288) : "memory");
        asm volatile("cp.async.bulk.commit_group;" ::: "memory");
        asm volatile("cp.async.bulk.wait_group.read 0;" ::: "memory");
        asm volatile("mbarrier.arrive.shared::cta.b64 _, [%0], 8;" :: "r"(bars + 8 * (B_EMPTY + 6 + w)) : "memory");
        asm volatile("cp.async.bulk.wait_group 0;" ::: "memory");
        asm volatile("fence.proxy.async.global;" ::: "memory");
        asm volatile("red.release.gpu.global.add.u32 [%0], 1;" :: "l"(&g_cnt[(C_KV + g) * 8]) : "memory");
        if (w) PROFT(52);
        poll_ge(&g_cnt[(C_KV + g) * 8], (ep + 1) * 32);
        if (w) PROFT(53);
      }
      __syncwarp();
      {
        const uint32_t kb = base + OFF_AUX;
        const int eq = lane % 6, dpo = lane / 6;
        #pragma unroll 1
        for (int i = lane + 32 * w; i < 880; i += 64) sts128(kb + i * 16, 0, 0, 0, 0);
        asm volatile("bar.sync 5, 64;" ::: "memory");
        if (lane < 30) {
          #pragma unroll 1
          for (int i = 4 * w; i < 4 * w + 4; i++) {
            const int h = i >> 1, d = 10 * i + 2 * dpo, n = eq < 5 ? 20 * h + 4 * eq : 80 + h;
            const uint4 u = ldg_relaxed(kvs + d * 24 + eq * 4), v = ldg_relaxed(kvs + d * 24 + 24 + eq * 4);
            const uint32_t ad = kb + (d >> 4) * 2816 + n * 32 + ((((d >> 3) ^ (n >> 2)) & 1) << 4) + (d & 7) * 2;
            const float zu = eq < 5 ? 0.f : __uint_as_float(u.y), zv = eq < 5 ? 0.f : __uint_as_float(v.y);
            asm volatile("st.shared.u32 [%0], %1;" :: "r"(ad), "r"(pack(__uint_as_float(u.x) + zu, __uint_as_float(v.x) + zv)) : "memory");
            if (eq < 5) {
              asm volatile("st.shared.u32 [%0], %1;" :: "r"(ad + 32), "r"(pack(__uint_as_float(u.y), __uint_as_float(v.y))) : "memory");
              asm volatile("st.shared.u32 [%0], %1;" :: "r"(ad + 64), "r"(pack(__uint_as_float(u.z), __uint_as_float(v.z))) : "memory");
              asm volatile("st.shared.u32 [%0], %1;" :: "r"(ad + 96), "r"(pack(__uint_as_float(u.w), __uint_as_float(v.w))) : "memory");
            }
          }
        }
        asm volatile("fence.proxy.async.shared::cta;" ::: "memory");
        __syncwarp();
        if (lane == 0) { mbar_arrive(bars + 8 * B_KVRDY); }
      }
      if (lane == 0) {
        if (!w) {
          #pragma unroll 1
          for (int e = 1; e < nev; e++) {
            const int c = e == nev - 1 ? C_O + 2 * rb + role : C_H + rb * 3 + (e - 1);
            mbar_wait(bars + 8 * (B_EV + e), 0);
            mbar_wait(bars + 8 * (B_EV + 5 + e), 0);
            asm volatile("red.release.gpu.global.add.u32 [%0], 1;" :: "l"(&g_cnt[c * 8]) : "memory");
          }
        } else {
          #pragma unroll 1
          for (int i = 0; i < 4; i++) {
            poll_ge(&g_cnt[(i < 2 ? C_H + rb * 3 + 1 + i - role : C_O + 2 * rb + 3 - i) * 8], (ep + 1) * (i == 0 || (i == 1 && role) ? 8 : 4));
            mbar_arrive(bars + 8 * (B_OK + i));
          }
        }
      }
    PROFEND();
  }
}

typedef CUresult (*EncFn)(CUtensorMap*, CUtensorMapDataType, cuuint32_t, void*, const cuuint64_t*, const cuuint64_t*, const cuuint32_t*,
                          const cuuint32_t*, CUtensorMapInterleave, CUtensorMapSwizzle, CUtensorMapL2promotion, CUtensorMapFloatOOBfill);

CUtensorMap make_map(EncFn enc, const void* p, int rows, int cols, int box_r, int box_c, CUtensorMapSwizzle swz) {
  CUtensorMap m;
  cuuint64_t dims[2] = {(cuuint64_t)cols, (cuuint64_t)rows};
  cuuint64_t str[1] = {(cuuint64_t)cols * 2};
  cuuint32_t box[2] = {(cuuint32_t)box_c, (cuuint32_t)box_r};
  cuuint32_t es[2] = {1, 1};
  enc(&m, CU_TENSOR_MAP_DATA_TYPE_BFLOAT16, 2, const_cast<void*>(p), dims, str, box, es, CU_TENSOR_MAP_INTERLEAVE_NONE, swz,
      CU_TENSOR_MAP_L2_PROMOTION_L2_128B, CU_TENSOR_MAP_FLOAT_OOB_FILL_NONE);
  return m;
}

}

extern "C" void kernel_launch(void* const* d_in, const int* in_sizes, int n_in, void* d_out, int out_size) {
  (void)in_sizes; (void)n_in; (void)out_size;
  static EncFn enc = nullptr;
  if (!enc) {
    cudaDriverEntryPointQueryResult q;
    cudaGetDriverEntryPoint("cuTensorMapEncodeTiled", (void**)&enc, cudaEnableDefault, &q);
    cudaFuncSetAttribute(fused_kernel, cudaFuncAttributeMaxDynamicSharedMemorySize, SMEM_BYTES);
  }
  Maps M;
  {
    cuuint64_t dims[3] = {64, (cuuint64_t)S_, 10}, str[2] = {D_ * 2, 128};
    cuuint32_t box[3] = {64, 64, 2}, es[3] = {1, 1, 1};
    enc(&M.x, CU_TENSOR_MAP_DATA_TYPE_BFLOAT16, 3, d_in[0], dims, str, box, es, CU_TENSOR_MAP_INTERLEAVE_NONE, CU_TENSOR_MAP_SWIZZLE_128B,
        CU_TENSOR_MAP_L2_PROMOTION_L2_128B, CU_TENSOR_MAP_FLOAT_OOB_FILL_NONE);
  }
  M.qkv64 = make_map(enc, d_in[1], D_, 3 * D_, 80, 64, CU_TENSOR_MAP_SWIZZLE_128B);
  M.qkv16 = make_map(enc, d_in[1], D_, 3 * D_, 80, 16, CU_TENSOR_MAP_SWIZZLE_128B);
  M.woa = make_map(enc, d_in[2], D_, D_, 80, 64, CU_TENSOR_MAP_SWIZZLE_128B);
  M.wob = make_map(enc, d_in[2], D_, D_, 80, 16, CU_TENSOR_MAP_SWIZZLE_128B);
  M.w1a = make_map(enc, d_in[4], D_, F_, 80, 64, CU_TENSOR_MAP_SWIZZLE_128B);
  M.w1b = make_map(enc, d_in[4], D_, F_, 80, 32, CU_TENSOR_MAP_SWIZZLE_128B);
  M.w3a = make_map(enc, d_in[5], D_, F_, 80, 64, CU_TENSOR_MAP_SWIZZLE_128B);
  M.w3b = make_map(enc, d_in[5], D_, F_, 80, 32, CU_TENSOR_MAP_SWIZZLE_128B);
  M.w1c = make_map(enc, d_in[4], D_, F_, 80, 48, CU_TENSOR_MAP_SWIZZLE_128B);
  M.w3c = make_map(enc, d_in[5], D_, F_, 80, 48, CU_TENSOR_MAP_SWIZZLE_128B);
  M.w2a = make_map(enc, d_in[6], F_, D_, 64, 64, CU_TENSOR_MAP_SWIZZLE_128B);
  M.w2b = make_map(enc, d_in[6], F_, D_, 64, 32, CU_TENSOR_MAP_SWIZZLE_64B);
  M.xa = make_map(enc, d_in[0], S_, D_, 128, 64, CU_TENSOR_MAP_SWIZZLE_128B);
  M.xb = make_map(enc, d_in[0], S_, D_, 128, 16, CU_TENSOR_MAP_SWIZZLE_32B);
  fused_kernel<<<128, 384, SMEM_BYTES>>>(M, (char*)d_out);
}
```
